```python
import torch

def _softmax(x, axis=-1):
    return torch.softmax(x, dim=axis)
def _gelu(x):
    return torch.nn.functional.gelu(x, approximate="tanh")
def _silu(x):
    return torch.nn.functional.silu(x)
def _sigmoid(x):
    return torch.sigmoid(x)
def _layernorm(x, axis=-1, eps=1e-5):
    m = x.mean(dim=axis, keepdim=True)
    v = x.var(dim=axis, keepdim=True, unbiased=False)
    return (x - m) / torch.sqrt(v + eps)
def _scatter_add(tgt, idx, src, axis=0):
    return tgt.clone().index_add_(axis, idx, src)
def _segment_sum(src, seg, n):
    out = torch.zeros((n,) + src.shape[1:], dtype=src.dtype)
    return out.index_add_(0, seg, src)
def _pad(x, pw):
    flat = tuple(v for pair in reversed(pw) for v in pair)
    return torch.nn.functional.pad(x, flat)

kernel_name = 'sequential_preLN__spectral_gfnet__glu_gated_swiglu__prompt'

def setup_inputs():

    _w = (lambda a: (lambda t: t.to(torch.bfloat16) if t.is_floating_point() else t)(torch.as_tensor(a)))
    def _A_setup():
        B, S, D = 1, 2048, 640
        Df = D // 2 + 1
        return {
            "x": _w((lambda *s: torch.randn(*s, dtype=torch.bfloat16) * 0.05)(B, S, D)),
            "w_r": _w((lambda *s: torch.randn(*s, dtype=torch.bfloat16) * 0.4)(S, Df) * 0.02),
            "w_i": _w((lambda *s: torch.randn(*s, dtype=torch.bfloat16) * 0.4)(S, Df) * 0.02),
        }
    _A_in = _A_setup()

    def _B_setup():
        B, S, D, F = 1, 2048, 640, 1536
        return {
            "x": _w((lambda *s: torch.randn(*s, dtype=torch.bfloat16) * 0.05)(B, S, D)),
            "w1": _w((lambda *s: torch.randn(*s, dtype=torch.bfloat16) * 0.2)(D, F) * (2.0 / D) ** 0.5),
            "w3": _w((lambda *s: torch.randn(*s, dtype=torch.bfloat16) * 0.2)(D, F) * (2.0 / D) ** 0.5),
            "w2": _w((lambda *s: torch.randn(*s, dtype=torch.bfloat16) * 0.2)(F, D) * (2.0 / F) ** 0.5),
        }
    _B_in = _B_setup()

    return {
        "A_x": _A_in["x"],
        "A_w_r": _A_in["w_r"],
        "A_w_i": _A_in["w_i"],
        "B_x": _B_in["x"],
        "B_w1": _B_in["w1"],
        "B_w3": _B_in["w3"],
        "B_w2": _B_in["w2"],
    }

def reference(A_x, A_w_r, A_w_i, B_x, B_w1, B_w3, B_w2):
    def _A_ref(x, w_r, w_i):
        B, S, D = x.shape
        X = (lambda x, axes=(-2,-1): torch.fft.rfft2(x.float(), dim=axes))(x, axes=(-2, -1))
        W = w_r + 1j * w_i
        X = X * W
        y = (lambda x, s, axes=(-2,-1): torch.fft.irfft2(x, s=s, dim=axes).to(torch.bfloat16))(X, (S, D), axes=(-2, -1))
        return y

    def _B_ref(x, w1, w3, w2):
        gate = torch.einsum("bsd,df->bsf", x, w1)
        up = torch.einsum("bsd,df->bsf", x, w3)
        h = _silu(gate) * up
        out = torch.einsum("bsf,fd->bsd", h, w2)
        return out

    x = A_x
    h = x + _A_ref(_layernorm(x, axis=-1), A_w_r, A_w_i)
    h2 = h + _B_ref(_layernorm(h, axis=-1), B_w1, B_w3, B_w2)
    return h2
```

```cpp
#include <cuda_runtime.h>
#include <cuda_bf16.h>
#include <cuda.h>
#include <stdint.h>

typedef __nv_bfloat16 bf16;

__device__ __forceinline__ uint32_t smem_u32(const void* p) { return (uint32_t)__cvta_generic_to_shared(p); }
__device__ __forceinline__ void mbar_init(uint32_t bar, uint32_t cnt) { asm volatile("mbarrier.init.shared::cta.b64 [%0], %1;" ::"r"(bar), "r"(cnt) : "memory"); }
__device__ __forceinline__ void mbar_expect_tx(uint32_t bar, uint32_t bytes) { asm volatile("mbarrier.arrive.expect_tx.shared::cta.b64 _, [%0], %1;" ::"r"(bar), "r"(bytes) : "memory"); }
__device__ __forceinline__ void mbar_arrive(uint32_t bar) { asm volatile("mbarrier.arrive.shared::cta.b64 _, [%0];" ::"r"(bar) : "memory"); }
__device__ __forceinline__ void mbar_arrive_cluster(uint32_t bar, uint32_t cta) {
    asm volatile("{\n.reg .b32 ra;\nmapa.shared::cluster.u32 ra, %0, %1;\nmbarrier.arrive.shared::cluster.b64 _, [ra];\n}\n" ::"r"(bar), "r"(cta) : "memory");
}
__device__ __forceinline__ void mbar_wait(uint32_t bar, uint32_t parity) {
    asm volatile("{\n.reg .pred P1;\nLAB_WAIT:\nmbarrier.try_wait.parity.shared::cta.b64 P1, [%0], %1;\n@P1 bra DONE;\nbra LAB_WAIT;\nDONE:\n}\n" ::"r"(bar), "r"(parity) : "memory");
}
__device__ __forceinline__ void tma_load_2d(uint32_t dst, const CUtensorMap* tm, uint32_t bar, int c0, int c1) {
    asm volatile("cp.async.bulk.tensor.2d.shared::cluster.global.mbarrier::complete_tx::bytes [%0], [%1, {%3, %4}], [%2];" ::"r"(dst), "l"(tm), "r"(bar), "r"(c0), "r"(c1) : "memory");
}
__device__ __forceinline__ void tma_load_3d(uint32_t dst, const CUtensorMap* tm, uint32_t bar, int c0, int c1, int c2) {
    asm volatile("cp.async.bulk.tensor.3d.shared::cluster.global.mbarrier::complete_tx::bytes [%0], [%1, {%3, %4, %5}], [%2];" ::"r"(dst), "l"(tm), "r"(bar), "r"(c0), "r"(c1), "r"(c2) : "memory");
}
__device__ __forceinline__ void bulk_load(uint32_t dst, const void* src, uint32_t bytes, uint32_t bar) {
    asm volatile("cp.async.bulk.shared::cluster.global.mbarrier::complete_tx::bytes [%0], [%1], %2, [%3];" ::"r"(dst), "l"(src), "r"(bytes), "r"(bar) : "memory");
}
__device__ __forceinline__ void fence_proxy_async_smem() { asm volatile("fence.proxy.async.shared::cta;" ::: "memory"); }
__device__ __forceinline__ void fence_mbar_init() { asm volatile("fence.mbarrier_init.release.cluster;" ::: "memory"); }
__device__ __forceinline__ void wgmma_fence() { asm volatile("wgmma.fence.sync.aligned;" ::: "memory"); }
__device__ __forceinline__ void wgmma_commit() { asm volatile("wgmma.commit_group.sync.aligned;" ::: "memory"); }
template <int N> __device__ __forceinline__ void wgmma_wait() { asm volatile("wgmma.wait_group.sync.aligned %0;" ::"n"(N) : "memory"); }
template <int R> __device__ __forceinline__ void reg_alloc() { asm volatile("setmaxnreg.inc.sync.aligned.u32 %0;" ::"n"(R)); }
template <int R> __device__ __forceinline__ void reg_dealloc() { asm volatile("setmaxnreg.dec.sync.aligned.u32 %0;" ::"n"(R)); }
__device__ __forceinline__ void named_bar_sync(int id, int n) { asm volatile("bar.sync %0, %1;" ::"r"(id), "r"(n) : "memory"); }
__device__ __forceinline__ void pdl_wait() { asm volatile("griddepcontrol.wait;" ::: "memory"); }
__device__ __forceinline__ void pdl_launch() { asm volatile("griddepcontrol.launch_dependents;" ::: "memory"); }
__device__ __forceinline__ void stmatrix_x4(uint32_t addr, uint32_t r0, uint32_t r1, uint32_t r2, uint32_t r3) {
    asm volatile("stmatrix.sync.aligned.m8n8.x4.shared.b16 [%0], {%1, %2, %3, %4};" ::"r"(addr), "r"(r0), "r"(r1), "r"(r2), "r"(r3) : "memory");
}
__device__ __forceinline__ void stmatrix_x4_trans(uint32_t addr, uint32_t r0, uint32_t r1, uint32_t r2, uint32_t r3) {
    asm volatile("stmatrix.sync.aligned.m8n8.x4.trans.shared.b16 [%0], {%1, %2, %3, %4};" ::"r"(addr), "r"(r0), "r"(r1), "r"(r2), "r"(r3) : "memory");
}
__device__ __forceinline__ void ldmatrix_x4_trans(uint32_t addr, uint32_t& r0, uint32_t& r1, uint32_t& r2, uint32_t& r3) {
    asm volatile("ldmatrix.sync.aligned.m8n8.x4.trans.shared.b16 {%0, %1, %2, %3}, [%4];" : "=r"(r0), "=r"(r1), "=r"(r2), "=r"(r3) : "r"(addr) : "memory");
}
__device__ __forceinline__ uint64_t make_desc(uint32_t addr, uint32_t lbo_bytes, uint32_t sbo_bytes, int swz) {
    uint64_t d = 0;
    d |= (uint64_t)((addr & 0x3FFFF) >> 4);
    d |= (uint64_t)((lbo_bytes & 0x3FFFF) >> 4) << 16;
    d |= (uint64_t)((sbo_bytes & 0x3FFFF) >> 4) << 32;
    d |= (uint64_t)swz << 62;
    return d;
}
__device__ __forceinline__ uint32_t pack_bf16(float lo, float hi) {
    uint32_t r;
    asm("cvt.rn.bf16x2.f32 %0, %1, %2;" : "=r"(r) : "f"(hi), "f"(lo));
    return r;
}
__device__ __forceinline__ float bf_lo(uint32_t v) { return __uint_as_float(v << 16); }
__device__ __forceinline__ float bf_hi(uint32_t v) { return __uint_as_float(v & 0xffff0000u); }
__device__ __forceinline__ float round_bf16(float v) { return __bfloat162float(__float2bfloat16_rn(v)); }
template <int NR> __device__ __forceinline__ void fence_regs(float* d) {
#pragma unroll
    for (int i = 0; i < NR; i++) asm volatile("" : "+f"(d[i])::"memory");
}

template<int TB> __device__ __forceinline__ void wgmma_rs_bf16_n40(float* d, const uint32_t* a, uint64_t db, int scaleD) {
  asm volatile("{\n.reg .pred p;\nsetp.ne.b32 p, %25, 0;\n"
    "wgmma.mma_async.sync.aligned.m64n40k16.f32.bf16.bf16 {%0, %1, %2, %3, %4, %5, %6, %7, %8, %9, %10, %11, %12, %13, %14, %15, %16, %17, %18, %19}, {%20, %21, %22, %23}, %24, p, 1, 1, %26;\n}\n"
    : "+f"(d[0]), "+f"(d[1]), "+f"(d[2]), "+f"(d[3]), "+f"(d[4]), "+f"(d[5]), "+f"(d[6]), "+f"(d[7]), "+f"(d[8]), "+f"(d[9]), "+f"(d[10]), "+f"(d[11]), "+f"(d[12]), "+f"(d[13]), "+f"(d[14]), "+f"(d[15]), "+f"(d[16]), "+f"(d[17]), "+f"(d[18]), "+f"(d[19])
    : "r"(a[0]), "r"(a[1]), "r"(a[2]), "r"(a[3]), "l"(db), "r"(scaleD), "n"(TB));
}
template<int TB> __device__ __forceinline__ void wgmma_rs_bf16_n64(float* d, const uint32_t* a, uint64_t db, int scaleD) {
  asm volatile("{\n.reg .pred p;\nsetp.ne.b32 p, %37, 0;\n"
    "wgmma.mma_async.sync.aligned.m64n64k16.f32.bf16.bf16 {%0, %1, %2, %3, %4, %5, %6, %7, %8, %9, %10, %11, %12, %13, %14, %15, %16, %17, %18, %19, %20, %21, %22, %23, %24, %25, %26, %27, %28, %29, %30, %31}, {%32, %33, %34, %35}, %36, p, 1, 1, %38;\n}\n"
    : "+f"(d[0]), "+f"(d[1]), "+f"(d[2]), "+f"(d[3]), "+f"(d[4]), "+f"(d[5]), "+f"(d[6]), "+f"(d[7]), "+f"(d[8]), "+f"(d[9]), "+f"(d[10]), "+f"(d[11]), "+f"(d[12]), "+f"(d[13]), "+f"(d[14]), "+f"(d[15]), "+f"(d[16]), "+f"(d[17]), "+f"(d[18]), "+f"(d[19]), "+f"(d[20]), "+f"(d[21]), "+f"(d[22]), "+f"(d[23]), "+f"(d[24]), "+f"(d[25]), "+f"(d[26]), "+f"(d[27]), "+f"(d[28]), "+f"(d[29]), "+f"(d[30]), "+f"(d[31])
    : "r"(a[0]), "r"(a[1]), "r"(a[2]), "r"(a[3]), "l"(db), "r"(scaleD), "n"(TB));
}
template<int TB> __device__ __forceinline__ void wgmma_rs_bf16_n80(float* d, const uint32_t* a, uint64_t db, int scaleD) {
  asm volatile("{\n.reg .pred p;\nsetp.ne.b32 p, %45, 0;\n"
    "wgmma.mma_async.sync.aligned.m64n80k16.f32.bf16.bf16 {%0, %1, %2, %3, %4, %5, %6, %7, %8, %9, %10, %11, %12, %13, %14, %15, %16, %17, %18, %19, %20, %21, %22, %23, %24, %25, %26, %27, %28, %29, %30, %31, %32, %33, %34, %35, %36, %37, %38, %39}, {%40, %41, %42, %43}, %44, p, 1, 1, %46;\n}\n"
    : "+f"(d[0]), "+f"(d[1]), "+f"(d[2]), "+f"(d[3]), "+f"(d[4]), "+f"(d[5]), "+f"(d[6]), "+f"(d[7]), "+f"(d[8]), "+f"(d[9]), "+f"(d[10]), "+f"(d[11]), "+f"(d[12]), "+f"(d[13]), "+f"(d[14]), "+f"(d[15]), "+f"(d[16]), "+f"(d[17]), "+f"(d[18]), "+f"(d[19]), "+f"(d[20]), "+f"(d[21]), "+f"(d[22]), "+f"(d[23]), "+f"(d[24]), "+f"(d[25]), "+f"(d[26]), "+f"(d[27]), "+f"(d[28]), "+f"(d[29]), "+f"(d[30]), "+f"(d[31]), "+f"(d[32]), "+f"(d[33]), "+f"(d[34]), "+f"(d[35]), "+f"(d[36]), "+f"(d[37]), "+f"(d[38]), "+f"(d[39])
    : "r"(a[0]), "r"(a[1]), "r"(a[2]), "r"(a[3]), "l"(db), "r"(scaleD), "n"(TB));
}
template<int TB> __device__ __forceinline__ void wgmma_rs_bf16_n128(float* d, const uint32_t* a, uint64_t db, int scaleD) {
  asm volatile("{\n.reg .pred p;\nsetp.ne.b32 p, %69, 0;\n"
    "wgmma.mma_async.sync.aligned.m64n128k16.f32.bf16.bf16 {%0, %1, %2, %3, %4, %5, %6, %7, %8, %9, %10, %11, %12, %13, %14, %15, %16, %17, %18, %19, %20, %21, %22, %23, %24, %25, %26, %27, %28, %29, %30, %31, %32, %33, %34, %35, %36, %37, %38, %39, %40, %41, %42, %43, %44, %45, %46, %47, %48, %49, %50, %51, %52, %53, %54, %55, %56, %57, %58, %59, %60, %61, %62, %63}, {%64, %65, %66, %67}, %68, p, 1, 1, %70;\n}\n"
    : "+f"(d[0]), "+f"(d[1]), "+f"(d[2]), "+f"(d[3]), "+f"(d[4]), "+f"(d[5]), "+f"(d[6]), "+f"(d[7]), "+f"(d[8]), "+f"(d[9]), "+f"(d[10]), "+f"(d[11]), "+f"(d[12]), "+f"(d[13]), "+f"(d[14]), "+f"(d[15]), "+f"(d[16]), "+f"(d[17]), "+f"(d[18]), "+f"(d[19]), "+f"(d[20]), "+f"(d[21]), "+f"(d[22]), "+f"(d[23]), "+f"(d[24]), "+f"(d[25]), "+f"(d[26]), "+f"(d[27]), "+f"(d[28]), "+f"(d[29]), "+f"(d[30]), "+f"(d[31]), "+f"(d[32]), "+f"(d[33]), "+f"(d[34]), "+f"(d[35]), "+f"(d[36]), "+f"(d[37]), "+f"(d[38]), "+f"(d[39]), "+f"(d[40]), "+f"(d[41]), "+f"(d[42]), "+f"(d[43]), "+f"(d[44]), "+f"(d[45]), "+f"(d[46]), "+f"(d[47]), "+f"(d[48]), "+f"(d[49]), "+f"(d[50]), "+f"(d[51]), "+f"(d[52]), "+f"(d[53]), "+f"(d[54]), "+f"(d[55]), "+f"(d[56]), "+f"(d[57]), "+f"(d[58]), "+f"(d[59]), "+f"(d[60]), "+f"(d[61]), "+f"(d[62]), "+f"(d[63])
    : "r"(a[0]), "r"(a[1]), "r"(a[2]), "r"(a[3]), "l"(db), "r"(scaleD), "n"(TB));
}
template<int TA, int TB> __device__ __forceinline__ void wgmma_ss_bf16_n256(float* d, uint64_t da, uint64_t db, int scaleD) {
  asm volatile("{\n.reg .pred p;\nsetp.ne.b32 p, %130, 0;\n"
    "wgmma.mma_async.sync.aligned.m64n256k16.f32.bf16.bf16 {%0, %1, %2, %3, %4, %5, %6, %7, %8, %9, %10, %11, %12, %13, %14, %15, %16, %17, %18, %19, %20, %21, %22, %23, %24, %25, %26, %27, %28, %29, %30, %31, %32, %33, %34, %35, %36, %37, %38, %39, %40, %41, %42, %43, %44, %45, %46, %47, %48, %49, %50, %51, %52, %53, %54, %55, %56, %57, %58, %59, %60, %61, %62, %63, %64, %65, %66, %67, %68, %69, %70, %71, %72, %73, %74, %75, %76, %77, %78, %79, %80, %81, %82, %83, %84, %85, %86, %87, %88, %89, %90, %91, %92, %93, %94, %95, %96, %97, %98, %99, %100, %101, %102, %103, %104, %105, %106, %107, %108, %109, %110, %111, %112, %113, %114, %115, %116, %117, %118, %119, %120, %121, %122, %123, %124, %125, %126, %127}, %128, %129, p, 1, 1, %131, %132;\n}\n"
    : "+f"(d[0]), "+f"(d[1]), "+f"(d[2]), "+f"(d[3]), "+f"(d[4]), "+f"(d[5]), "+f"(d[6]), "+f"(d[7]), "+f"(d[8]), "+f"(d[9]), "+f"(d[10]), "+f"(d[11]), "+f"(d[12]), "+f"(d[13]), "+f"(d[14]), "+f"(d[15]), "+f"(d[16]), "+f"(d[17]), "+f"(d[18]), "+f"(d[19]), "+f"(d[20]), "+f"(d[21]), "+f"(d[22]), "+f"(d[23]), "+f"(d[24]), "+f"(d[25]), "+f"(d[26]), "+f"(d[27]), "+f"(d[28]), "+f"(d[29]), "+f"(d[30]), "+f"(d[31]), "+f"(d[32]), "+f"(d[33]), "+f"(d[34]), "+f"(d[35]), "+f"(d[36]), "+f"(d[37]), "+f"(d[38]), "+f"(d[39]), "+f"(d[40]), "+f"(d[41]), "+f"(d[42]), "+f"(d[43]), "+f"(d[44]), "+f"(d[45]), "+f"(d[46]), "+f"(d[47]), "+f"(d[48]), "+f"(d[49]), "+f"(d[50]), "+f"(d[51]), "+f"(d[52]), "+f"(d[53]), "+f"(d[54]), "+f"(d[55]), "+f"(d[56]), "+f"(d[57]), "+f"(d[58]), "+f"(d[59]), "+f"(d[60]), "+f"(d[61]), "+f"(d[62]), "+f"(d[63]), "+f"(d[64]), "+f"(d[65]), "+f"(d[66]), "+f"(d[67]), "+f"(d[68]), "+f"(d[69]), "+f"(d[70]), "+f"(d[71]), "+f"(d[72]), "+f"(d[73]), "+f"(d[74]), "+f"(d[75]), "+f"(d[76]), "+f"(d[77]), "+f"(d[78]), "+f"(d[79]), "+f"(d[80]), "+f"(d[81]), "+f"(d[82]), "+f"(d[83]), "+f"(d[84]), "+f"(d[85]), "+f"(d[86]), "+f"(d[87]), "+f"(d[88]), "+f"(d[89]), "+f"(d[90]), "+f"(d[91]), "+f"(d[92]), "+f"(d[93]), "+f"(d[94]), "+f"(d[95]), "+f"(d[96]), "+f"(d[97]), "+f"(d[98]), "+f"(d[99]), "+f"(d[100]), "+f"(d[101]), "+f"(d[102]), "+f"(d[103]), "+f"(d[104]), "+f"(d[105]), "+f"(d[106]), "+f"(d[107]), "+f"(d[108]), "+f"(d[109]), "+f"(d[110]), "+f"(d[111]), "+f"(d[112]), "+f"(d[113]), "+f"(d[114]), "+f"(d[115]), "+f"(d[116]), "+f"(d[117]), "+f"(d[118]), "+f"(d[119]), "+f"(d[120]), "+f"(d[121]), "+f"(d[122]), "+f"(d[123]), "+f"(d[124]), "+f"(d[125]), "+f"(d[126]), "+f"(d[127])
    : "l"(da), "l"(db), "r"(scaleD), "n"(TA), "n"(TB));
}
template<int TA, int TB> __device__ __forceinline__ void wgmma_ss_bf16_n128(float* d, uint64_t da, uint64_t db, int scaleD) {
  asm volatile("{\n.reg .pred p;\nsetp.ne.b32 p, %66, 0;\n"
    "wgmma.mma_async.sync.aligned.m64n128k16.f32.bf16.bf16 {%0, %1, %2, %3, %4, %5, %6, %7, %8, %9, %10, %11, %12, %13, %14, %15, %16, %17, %18, %19, %20, %21, %22, %23, %24, %25, %26, %27, %28, %29, %30, %31, %32, %33, %34, %35, %36, %37, %38, %39, %40, %41, %42, %43, %44, %45, %46, %47, %48, %49, %50, %51, %52, %53, %54, %55, %56, %57, %58, %59, %60, %61, %62, %63}, %64, %65, p, 1, 1, %67, %68;\n}\n"
    : "+f"(d[0]), "+f"(d[1]), "+f"(d[2]), "+f"(d[3]), "+f"(d[4]), "+f"(d[5]), "+f"(d[6]), "+f"(d[7]), "+f"(d[8]), "+f"(d[9]), "+f"(d[10]), "+f"(d[11]), "+f"(d[12]), "+f"(d[13]), "+f"(d[14]), "+f"(d[15]), "+f"(d[16]), "+f"(d[17]), "+f"(d[18]), "+f"(d[19]), "+f"(d[20]), "+f"(d[21]), "+f"(d[22]), "+f"(d[23]), "+f"(d[24]), "+f"(d[25]), "+f"(d[26]), "+f"(d[27]), "+f"(d[28]), "+f"(d[29]), "+f"(d[30]), "+f"(d[31]), "+f"(d[32]), "+f"(d[33]), "+f"(d[34]), "+f"(d[35]), "+f"(d[36]), "+f"(d[37]), "+f"(d[38]), "+f"(d[39]), "+f"(d[40]), "+f"(d[41]), "+f"(d[42]), "+f"(d[43]), "+f"(d[44]), "+f"(d[45]), "+f"(d[46]), "+f"(d[47]), "+f"(d[48]), "+f"(d[49]), "+f"(d[50]), "+f"(d[51]), "+f"(d[52]), "+f"(d[53]), "+f"(d[54]), "+f"(d[55]), "+f"(d[56]), "+f"(d[57]), "+f"(d[58]), "+f"(d[59]), "+f"(d[60]), "+f"(d[61]), "+f"(d[62]), "+f"(d[63])
    : "l"(da), "l"(db), "r"(scaleD), "n"(TA), "n"(TB));
}
template<int TA, int TB> __device__ __forceinline__ void wgmma_ss_bf16_n160(float* d, uint64_t da, uint64_t db, int scaleD) {
  asm volatile("{\n.reg .pred p;\nsetp.ne.b32 p, %82, 0;\n"
    "wgmma.mma_async.sync.aligned.m64n160k16.f32.bf16.bf16 {%0, %1, %2, %3, %4, %5, %6, %7, %8, %9, %10, %11, %12, %13, %14, %15, %16, %17, %18, %19, %20, %21, %22, %23, %24, %25, %26, %27, %28, %29, %30, %31, %32, %33, %34, %35, %36, %37, %38, %39, %40, %41, %42, %43, %44, %45, %46, %47, %48, %49, %50, %51, %52, %53, %54, %55, %56, %57, %58, %59, %60, %61, %62, %63, %64, %65, %66, %67, %68, %69, %70, %71, %72, %73, %74, %75, %76, %77, %78, %79}, %80, %81, p, 1, 1, %83, %84;\n}\n"
    : "+f"(d[0]), "+f"(d[1]), "+f"(d[2]), "+f"(d[3]), "+f"(d[4]), "+f"(d[5]), "+f"(d[6]), "+f"(d[7]), "+f"(d[8]), "+f"(d[9]), "+f"(d[10]), "+f"(d[11]), "+f"(d[12]), "+f"(d[13]), "+f"(d[14]), "+f"(d[15]), "+f"(d[16]), "+f"(d[17]), "+f"(d[18]), "+f"(d[19]), "+f"(d[20]), "+f"(d[21]), "+f"(d[22]), "+f"(d[23]), "+f"(d[24]), "+f"(d[25]), "+f"(d[26]), "+f"(d[27]), "+f"(d[28]), "+f"(d[29]), "+f"(d[30]), "+f"(d[31]), "+f"(d[32]), "+f"(d[33]), "+f"(d[34]), "+f"(d[35]), "+f"(d[36]), "+f"(d[37]), "+f"(d[38]), "+f"(d[39]), "+f"(d[40]), "+f"(d[41]), "+f"(d[42]), "+f"(d[43]), "+f"(d[44]), "+f"(d[45]), "+f"(d[46]), "+f"(d[47]), "+f"(d[48]), "+f"(d[49]), "+f"(d[50]), "+f"(d[51]), "+f"(d[52]), "+f"(d[53]), "+f"(d[54]), "+f"(d[55]), "+f"(d[56]), "+f"(d[57]), "+f"(d[58]), "+f"(d[59]), "+f"(d[60]), "+f"(d[61]), "+f"(d[62]), "+f"(d[63]), "+f"(d[64]), "+f"(d[65]), "+f"(d[66]), "+f"(d[67]), "+f"(d[68]), "+f"(d[69]), "+f"(d[70]), "+f"(d[71]), "+f"(d[72]), "+f"(d[73]), "+f"(d[74]), "+f"(d[75]), "+f"(d[76]), "+f"(d[77]), "+f"(d[78]), "+f"(d[79])
    : "l"(da), "l"(db), "r"(scaleD), "n"(TA), "n"(TB));
}


__device__ __align__(1024) bf16 g_Z[321 * 2 * 32 * 64];
__device__ __align__(1024) uint32_t g_Wt[321 * 128 * 16];
__device__ __align__(1024) bf16 g_V[640 * 128 * 16];
__device__ __align__(1024) bf16 g_h[2048 * 640];
__device__ __align__(1024) bf16 g_hn[2048 * 640];
__device__ __align__(1024) bf16 g_g[2048 * 1536];
__device__ __align__(1024) uint4 g_part[128 * 10 * 256];
__device__ __align__(128) unsigned g_flags[96 * 32 + 128];

__device__ __align__(128) const uint32_t T_A32[2048] = {
0x3f803f80,0x80008000,0,0x3f803f80,0x3f803f80,0x80008000,0,0x3f803f80,0x3f803f80,0x80008000,0,0x3f803f80,
0x3f803f80,0x80008000,0,0x3f803f80,0x3f7b3f80,0xbe488000,0x3e480000,0x3f7b3f80,0x3f553f6d,0xbf0ebec4,0x3f0e3ec4,0x3f553f6d,
0x3f0e3f35,0xbf55bf35,0x3f553f35,0x3f0e3f35,0x3e483ec4,0xbf7bbf6d,0x3f7b3f6d,0x3e483ec4,0x3f6d3f80,0xbec48000,0x3ec40000,0x3f6d3f80,
0x3ec43f35,0xbf6dbf35,0x3f6d3f35,0x3ec43f35,0xbec4248d,0xbf6dbf80,0x3f6d3f80,0xbec4248d,0xbf6dbf35,0xbec4bf35,0x3ec43f35,0xbf6dbf35,
0x3f553f80,0xbf0e8000,0x3f0e0000,0x3f553f80,0xbe483ec4,0xbf7bbf6d,0x3f7b3f6d,0xbe483ec4,0xbf7bbf35,0xbe48bf35,0x3e483f35,0xbf7bbf35,
0xbf0ebf6d,0x3f553ec4,0xbf55bec4,0xbf0ebf6d,0x3f353f80,0xbf358000,0x3f350000,0x3f353f80,0xbf35248d,0xbf35bf80,0x3f353f80,0xbf35248d,
0xbf35bf80,0x3f35a50d,0xbf35250d,0xbf35bf80,0x3f35a554,0x3f353f80,0xbf35bf80,0x3f35a554,0x3f0e3f80,0xbf558000,0x3f550000,0x3f0e3f80,
0xbf7bbec4,0xbe48bf6d,0x3e483f6d,0xbf7bbec4,0x3e48bf35,0x3f7b3f35,0xbf7bbf35,0x3e48bf35,0x3f553f6d,0xbf0e3ec4,0x3f0ebec4,0x3f553f6d,
0x3ec43f80,0xbf6d8000,0x3f6d0000,0x3ec43f80,0xbf6dbf35,0x3ec4bf35,0xbec43f35,0xbf6dbf35,0x3f6da554,0x3ec43f80,0xbec4bf80,0x3f6da554,
0xbec43f35,0xbf6dbf35,0x3f6d3f35,0xbec43f35,0x3e483f80,0xbf7b8000,0x3f7b0000,0x3e483f80,0xbf0ebf6d,0x3f55bec4,0xbf553ec4,0xbf0ebf6d,
0x3f553f35,0xbf0e3f35,0x3f0ebf35,0x3f553f35,0xbf7bbec4,0x3e48bf6d,0xbe483f6d,0xbf7bbec4,0x248d3f80,0xbf808000,0x3f800000,0x248d3f80,
0xa554bf80,0x3f80a50d,0xbf80250d,0xa554bf80,0x248d3f80,0xbf808000,0x3f800000,0x248d3f80,0xa554bf80,0x3f80a50d,0xbf80250d,0xa554bf80,
0xbe483f80,0xbf7b8000,0x3f7b0000,0xbe483f80,0x3f0ebf6d,0x3f553ec4,0xbf55bec4,0x3f0ebf6d,0xbf553f35,0xbf0ebf35,0x3f0e3f35,0xbf553f35,
0x3f7bbec4,0x3e483f6d,0xbe48bf6d,0x3f7bbec4,0xbec43f80,0xbf6d8000,0x3f6d0000,0xbec43f80,0x3f6dbf35,0x3ec43f35,0xbec4bf35,0x3f6dbf35,
0xbf6d248d,0x3ec4bf80,0xbec43f80,0xbf6d248d,0x3ec43f35,0xbf6d3f35,0x3f6dbf35,0x3ec43f35,0xbf0e3f80,0xbf558000,0x3f550000,0xbf0e3f80,
0x3f7bbec4,0xbe483f6d,0x3e48bf6d,0x3f7bbec4,0xbe48bf35,0x3f7bbf35,0xbf7b3f35,0xbe48bf35,0xbf553f6d,0xbf0ebec4,0x3f0e3ec4,0xbf553f6d,
0xbf353f80,0xbf358000,0x3f350000,0xbf353f80,0x3f35a554,0xbf353f80,0x3f35bf80,0x3f35a554,0x3f35bf80,0x3f35a50d,0xbf35250d,0x3f35bf80,
0xbf35248d,0x3f35bf80,0xbf353f80,0xbf35248d,0xbf553f80,0xbf0e8000,0x3f0e0000,0xbf553f80,0x3e483ec4,0xbf7b3f6d,0x3f7bbf6d,0x3e483ec4,
0x3f7bbf35,0xbe483f35,0x3e48bf35,0x3f7bbf35,0x3f0ebf6d,0x3f55bec4,0xbf553ec4,0x3f0ebf6d,0xbf6d3f80,0xbec48000,0x3ec40000,0xbf6d3f80,
0xbec43f35,0xbf6d3f35,0x3f6dbf35,0xbec43f35,0x3ec4a554,0xbf6d3f80,0x3f6dbf80,0x3ec4a554,0x3f6dbf35,0xbec43f35,0x3ec4bf35,0x3f6dbf35,
0xbf7b3f80,0xbe488000,0x3e480000,0xbf7b3f80,0xbf553f6d,0xbf0e3ec4,0x3f0ebec4,0xbf553f6d,0xbf0e3f35,0xbf553f35,0x3f55bf35,0xbf0e3f35,
0xbe483ec4,0xbf7b3f6d,0x3f7bbf6d,0xbe483ec4,0xbf803f80,0xa50d8000,0x250d0000,0xbf803f80,0xbf803f80,0xa50d8000,0x250d0000,0xbf803f80,
0xbf803f80,0xa50d8000,0x250d0000,0xbf803f80,0xbf803f80,0xa50d8000,0x250d0000,0xbf803f80,0xbf7b3f80,0x3e488000,0xbe480000,0xbf7b3f80,
0xbf553f6d,0x3f0ebec4,0xbf0e3ec4,0xbf553f6d,0xbf0e3f35,0x3f55bf35,0xbf553f35,0xbf0e3f35,0xbe483ec4,0x3f7bbf6d,0xbf7b3f6d,0xbe483ec4,
0xbf6d3f80,0x3ec48000,0xbec40000,0xbf6d3f80,0xbec43f35,0x3f6dbf35,0xbf6d3f35,0xbec43f35,0x3ec4248d,0x3f6dbf80,0xbf6d3f80,0x3ec4248d,
0x3f6dbf35,0x3ec4bf35,0xbec43f35,0x3f6dbf35,0xbf553f80,0x3f0e8000,0xbf0e0000,0xbf553f80,0x3e483ec4,0x3f7bbf6d,0xbf7b3f6d,0x3e483ec4,
0x3f7bbf35,0x3e48bf35,0xbe483f35,0x3f7bbf35,0x3f0ebf6d,0xbf553ec4,0x3f55bec4,0x3f0ebf6d,0xbf353f80,0x3f358000,0xbf350000,0xbf353f80,
0x3f35248d,0x3f35bf80,0xbf353f80,0x3f35248d,0x3f35bf80,0xbf35a50d,0x3f35250d,0x3f35bf80,0xbf35a554,0xbf353f80,0x3f35bf80,0xbf35a554,
0xbf0e3f80,0x3f558000,0xbf550000,0xbf0e3f80,0x3f7bbec4,0x3e48bf6d,0xbe483f6d,0x3f7bbec4,0xbe48bf35,0xbf7b3f35,0x3f7bbf35,0xbe48bf35,
0xbf553f6d,0x3f0e3ec4,0xbf0ebec4,0xbf553f6d,0xbec43f80,0x3f6d8000,0xbf6d0000,0xbec43f80,0x3f6dbf35,0xbec4bf35,0x3ec43f35,0x3f6dbf35,
0xbf6da554,0xbec43f80,0x3ec4bf80,0xbf6da554,0x3ec43f35,0x3f6dbf35,0xbf6d3f35,0x3ec43f35,0xbe483f80,0x3f7b8000,0xbf7b0000,0xbe483f80,
0x3f0ebf6d,0xbf55bec4,0x3f553ec4,0x3f0ebf6d,0xbf553f35,0x3f0e3f35,0xbf0ebf35,0xbf553f35,0x3f7bbec4,0xbe48bf6d,0x3e483f6d,0x3f7bbec4,
0xa5543f80,0x3f808000,0xbf800000,0xa5543f80,0x248dbf80,0xbf80a50d,0x3f80250d,0x248dbf80,0xa5543f80,0x3f808000,0xbf800000,0xa5543f80,
0x248dbf80,0xbf80a50d,0x3f80250d,0x248dbf80,0x3e483f80,0x3f7b8000,0xbf7b0000,0x3e483f80,0xbf0ebf6d,0xbf553ec4,0x3f55bec4,0xbf0ebf6d,
0x3f553f35,0x3f0ebf35,0xbf0e3f35,0x3f553f35,0xbf7bbec4,0xbe483f6d,0x3e48bf6d,0xbf7bbec4,0x3ec43f80,0x3f6d8000,0xbf6d0000,0x3ec43f80,
0xbf6dbf35,0xbec43f35,0x3ec4bf35,0xbf6dbf35,0x3f6d248d,0xbec4bf80,0x3ec43f80,0x3f6d248d,0xbec43f35,0x3f6d3f35,0xbf6dbf35,0xbec43f35,
0x3f0e3f80,0x3f558000,0xbf550000,0x3f0e3f80,0xbf7bbec4,0x3e483f6d,0xbe48bf6d,0xbf7bbec4,0x3e48bf35,0xbf7bbf35,0x3f7b3f35,0x3e48bf35,
0x3f553f6d,0x3f0ebec4,0xbf0e3ec4,0x3f553f6d,0x3f353f80,0x3f358000,0xbf350000,0x3f353f80,0xbf35a554,0x3f353f80,0xbf35bf80,0xbf35a554,
0xbf35bf80,0xbf35a50d,0x3f35250d,0xbf35bf80,0x3f35248d,0xbf35bf80,0x3f353f80,0x3f35248d,0x3f553f80,0x3f0e8000,0xbf0e0000,0x3f553f80,
0xbe483ec4,0x3f7b3f6d,0xbf7bbf6d,0xbe483ec4,0xbf7bbf35,0x3e483f35,0xbe48bf35,0xbf7bbf35,0xbf0ebf6d,0xbf55bec4,0x3f553ec4,0xbf0ebf6d,
0x3f6d3f80,0x3ec48000,0xbec40000,0x3f6d3f80,0x3ec43f35,0x3f6d3f35,0xbf6dbf35,0x3ec43f35,0xbec4a554,0x3f6d3f80,0xbf6dbf80,0xbec4a554,
0xbf6dbf35,0x3ec43f35,0xbec4bf35,0xbf6dbf35,0x3f7b3f80,0x3e488000,0xbe480000,0x3f7b3f80,0x3f553f6d,0x3f0e3ec4,0xbf0ebec4,0x3f553f6d,
0x3f0e3f35,0x3f553f35,0xbf55bf35,0x3f0e3f35,0x3e483ec4,0x3f7b3f6d,0xbf7bbf6d,0x3e483ec4,0x3f803f80,0x80008000,0,0x3f803f80,
0x3f803f80,0x80008000,0,0x3f803f80,0x3f803f80,0x80008000,0,0x3f803f80,0x3f803f80,0x80008000,0,0x3f803f80,
0xbe48248d,0xbf7bbf80,0x3f7b3f80,0xbe48248d,0xbf0ebec4,0xbf55bf6d,0x3f553f6d,0xbf0ebec4,0xbf55bf35,0xbf0ebf35,0x3f0e3f35,0xbf55bf35,
0xbf7bbf6d,0xbe48bec4,0x3e483ec4,0xbf7bbf6d,0xbf6dbf80,0x3ec4a50d,0xbec4250d,0xbf6dbf80,0xbec4bf35,0x3f6d3f35,0xbf6dbf35,0xbec4bf35,
0x3ec4a554,0x3f6d3f80,0xbf6dbf80,0x3ec4a554,0x3f6d3f35,0x3ec43f35,0xbec4bf35,0x3f6d3f35,0x3f0ea554,0x3f553f80,0xbf55bf80,0x3f0ea554,
0x3f7b3f6d,0xbe483ec4,0x3e48bec4,0x3f7b3f6d,0x3e483f35,0xbf7bbf35,0x3f7b3f35,0x3e483f35,0xbf55bec4,0xbf0ebf6d,0x3f0e3f6d,0xbf55bec4,
0x3f353f80,0xbf358000,0x3f350000,0x3f353f80,0xbf35248d,0xbf35bf80,0x3f353f80,0xbf35248d,0xbf35bf80,0x3f35a50d,0xbf35250d,0xbf35bf80,
0x3f35a554,0x3f353f80,0xbf35bf80,0x3f35a554,0xbf55248d,0xbf0ebf80,0x3f0e3f80,0xbf55248d,0xbe48bf6d,0x3f7b3ec4,0xbf7bbec4,0xbe48bf6d,
0x3f7b3f35,0xbe483f35,0x3e48bf35,0x3f7b3f35,0xbf0e3ec4,0xbf55bf6d,0x3f553f6d,0xbf0e3ec4,0xbec4bf80,0x3f6da50d,0xbf6d250d,0xbec4bf80,
0x3f6d3f35,0xbec43f35,0x3ec4bf35,0x3f6d3f35,0xbf6d248d,0xbec4bf80,0x3ec43f80,0xbf6d248d,0x3ec4bf35,0x3f6d3f35,0xbf6dbf35,0x3ec4bf35,
0x3f7ba554,0x3e483f80,0xbe48bf80,0x3f7ba554,0xbf553ec4,0xbf0ebf6d,0x3f0e3f6d,0xbf553ec4,0x3f0ebf35,0x3f553f35,0xbf55bf35,0x3f0ebf35,
0xbe483f6d,0xbf7bbec4,0x3f7b3ec4,0xbe483f6d,0x248d3f80,0xbf808000,0x3f800000,0x248d3f80,0xa554bf80,0x3f80a50d,0xbf80250d,0xa554bf80,
0x248d3f80,0xbf808000,0x3f800000,0x248d3f80,0xa554bf80,0x3f80a50d,0xbf80250d,0xa554bf80,0xbf7b248d,0x3e48bf80,0xbe483f80,0xbf7b248d,
0x3f553ec4,0xbf0e3f6d,0x3f0ebf6d,0x3f553ec4,0xbf0ebf35,0x3f55bf35,0xbf553f35,0xbf0ebf35,0x3e483f6d,0xbf7b3ec4,0x3f7bbec4,0x3e483f6d,
0x3ec4bf80,0x3f6da50d,0xbf6d250d,0x3ec4bf80,0xbf6d3f35,0xbec4bf35,0x3ec43f35,0xbf6d3f35,0x3f6da554,0xbec43f80,0x3ec4bf80,0x3f6da554,
0xbec4bf35,0x3f6dbf35,0xbf6d3f35,0xbec4bf35,0x3f55a554,0xbf0e3f80,0x3f0ebf80,0x3f55a554,0x3e48bf6d,0x3f7bbec4,0xbf7b3ec4,0x3e48bf6d,
0xbf7b3f35,0xbe48bf35,0x3e483f35,0xbf7b3f35,0x3f0e3ec4,0xbf553f6d,0x3f55bf6d,0x3f0e3ec4,0xbf353f80,0xbf358000,0x3f350000,0xbf353f80,
0x3f35a554,0xbf353f80,0x3f35bf80,0x3f35a554,0x3f35bf80,0x3f35a50d,0xbf35250d,0x3f35bf80,0xbf35248d,0x3f35bf80,0xbf353f80,0xbf35248d,
0xbf0e248d,0x3f55bf80,0xbf553f80,0xbf0e248d,0xbf7b3f6d,0xbe48bec4,0x3e483ec4,0xbf7b3f6d,0xbe483f35,0xbf7b3f35,0x3f7bbf35,0xbe483f35,
0x3f55bec4,0xbf0e3f6d,0x3f0ebf6d,0x3f55bec4,0x3f6dbf80,0x3ec4a50d,0xbec4250d,0x3f6dbf80,0x3ec4bf35,0x3f6dbf35,0xbf6d3f35,0x3ec4bf35,
0xbec4248d,0x3f6dbf80,0xbf6d3f80,0xbec4248d,0xbf6d3f35,0x3ec4bf35,0xbec43f35,0xbf6d3f35,0x3e48a554,0xbf7b3f80,0x3f7bbf80,0x3e48a554,
0x3f0ebec4,0xbf553f6d,0x3f55bf6d,0x3f0ebec4,0x3f55bf35,0xbf0e3f35,0x3f0ebf35,0x3f55bf35,0x3f7bbf6d,0xbe483ec4,0x3e48bec4,0x3f7bbf6d,
0xbf803f80,0xa50d8000,0x250d0000,0xbf803f80,0xbf803f80,0xa50d8000,0x250d0000,0xbf803f80,0xbf803f80,0xa50d8000,0x250d0000,0xbf803f80,
0xbf803f80,0xa50d8000,0x250d0000,0xbf803f80,0x3e48248d,0x3f7bbf80,0xbf7b3f80,0x3e48248d,0x3f0ebec4,0x3f55bf6d,0xbf553f6d,0x3f0ebec4,
0x3f55bf35,0x3f0ebf35,0xbf0e3f35,0x3f55bf35,0x3f7bbf6d,0x3e48bec4,0xbe483ec4,0x3f7bbf6d,0x3f6dbf80,0xbec4a50d,0x3ec4250d,0x3f6dbf80,
0x3ec4bf35,0xbf6d3f35,0x3f6dbf35,0x3ec4bf35,0xbec4a554,0xbf6d3f80,0x3f6dbf80,0xbec4a554,0xbf6d3f35,0xbec43f35,0x3ec4bf35,0xbf6d3f35,
0xbf0ea554,0xbf553f80,0x3f55bf80,0xbf0ea554,0xbf7b3f6d,0x3e483ec4,0xbe48bec4,0xbf7b3f6d,0xbe483f35,0x3f7bbf35,0xbf7b3f35,0xbe483f35,
0x3f55bec4,0x3f0ebf6d,0xbf0e3f6d,0x3f55bec4,0xbf353f80,0x3f358000,0xbf350000,0xbf353f80,0x3f35248d,0x3f35bf80,0xbf353f80,0x3f35248d,
0x3f35bf80,0xbf35a50d,0x3f35250d,0x3f35bf80,0xbf35a554,0xbf353f80,0x3f35bf80,0xbf35a554,0x3f55248d,0x3f0ebf80,0xbf0e3f80,0x3f55248d,
0x3e48bf6d,0xbf7b3ec4,0x3f7bbec4,0x3e48bf6d,0xbf7b3f35,0x3e483f35,0xbe48bf35,0xbf7b3f35,0x3f0e3ec4,0x3f55bf6d,0xbf553f6d,0x3f0e3ec4,
0x3ec4bf80,0xbf6da50d,0x3f6d250d,0x3ec4bf80,0xbf6d3f35,0x3ec43f35,0xbec4bf35,0xbf6d3f35,0x3f6d248d,0x3ec4bf80,0xbec43f80,0x3f6d248d,
0xbec4bf35,0xbf6d3f35,0x3f6dbf35,0xbec4bf35,0xbf7ba554,0xbe483f80,0x3e48bf80,0xbf7ba554,0x3f553ec4,0x3f0ebf6d,0xbf0e3f6d,0x3f553ec4,
0xbf0ebf35,0xbf553f35,0x3f55bf35,0xbf0ebf35,0x3e483f6d,0x3f7bbec4,0xbf7b3ec4,0x3e483f6d,0xa5543f80,0x3f808000,0xbf800000,0xa5543f80,
0x248dbf80,0xbf80a50d,0x3f80250d,0x248dbf80,0xa5543f80,0x3f808000,0xbf800000,0xa5543f80,0x248dbf80,0xbf80a50d,0x3f80250d,0x248dbf80,
0x3f7b248d,0xbe48bf80,0x3e483f80,0x3f7b248d,0xbf553ec4,0x3f0e3f6d,0xbf0ebf6d,0xbf553ec4,0x3f0ebf35,0xbf55bf35,0x3f553f35,0x3f0ebf35,
0xbe483f6d,0x3f7b3ec4,0xbf7bbec4,0xbe483f6d,0xbec4bf80,0xbf6da50d,0x3f6d250d,0xbec4bf80,0x3f6d3f35,0x3ec4bf35,0xbec43f35,0x3f6d3f35,
0xbf6da554,0x3ec43f80,0xbec4bf80,0xbf6da554,0x3ec4bf35,0xbf6dbf35,0x3f6d3f35,0x3ec4bf35,0xbf55a554,0x3f0e3f80,0xbf0ebf80,0xbf55a554,
0xbe48bf6d,0xbf7bbec4,0x3f7b3ec4,0xbe48bf6d,0x3f7b3f35,0x3e48bf35,0xbe483f35,0x3f7b3f35,0xbf0e3ec4,0x3f553f6d,0xbf55bf6d,0xbf0e3ec4,
0x3f353f80,0x3f358000,0xbf350000,0x3f353f80,0xbf35a554,0x3f353f80,0xbf35bf80,0xbf35a554,0xbf35bf80,0xbf35a50d,0x3f35250d,0xbf35bf80,
0x3f35248d,0xbf35bf80,0x3f353f80,0x3f35248d,0x3f0e248d,0xbf55bf80,0x3f553f80,0x3f0e248d,0x3f7b3f6d,0x3e48bec4,0xbe483ec4,0x3f7b3f6d,
0x3e483f35,0x3f7b3f35,0xbf7bbf35,0x3e483f35,0xbf55bec4,0x3f0e3f6d,0xbf0ebf6d,0xbf55bec4,0xbf6dbf80,0xbec4a50d,0x3ec4250d,0xbf6dbf80,
0xbec4bf35,0xbf6dbf35,0x3f6d3f35,0xbec4bf35,0x3ec4248d,0xbf6dbf80,0x3f6d3f80,0x3ec4248d,0x3f6d3f35,0xbec4bf35,0x3ec43f35,0x3f6d3f35,
0xbe48a554,0x3f7b3f80,0xbf7bbf80,0xbe48a554,0xbf0ebec4,0x3f553f6d,0xbf55bf6d,0xbf0ebec4,0xbf55bf35,0x3f0e3f35,0xbf0ebf35,0xbf55bf35,
0xbf7bbf6d,0x3e483ec4,0xbe48bec4,0xbf7bbf6d,0x3f803f80,0x80008000,0,0x3f803f80,0x3f803f80,0x80008000,0,0x3f803f80,
0x3f803f80,0x80008000,0,0x3f803f80,0x3f803f80,0x80008000,0,0x3f803f80,0xbf7bbf80,0x3e48a50d,0xbe48250d,0xbf7bbf80,
0xbf55bf6d,0x3f0e3ec4,0xbf0ebec4,0xbf55bf6d,0xbf0ebf35,0x3f553f35,0xbf55bf35,0xbf0ebf35,0xbe48bec4,0x3f7b3f6d,0xbf7bbf6d,0xbe48bec4,
0x3f6d3f80,0xbec48000,0x3ec40000,0x3f6d3f80,0x3ec43f35,0xbf6dbf35,0x3f6d3f35,0x3ec43f35,0xbec4248d,0xbf6dbf80,0x3f6d3f80,0xbec4248d,
0xbf6dbf35,0xbec4bf35,0x3ec43f35,0xbf6dbf35,0xbf55bf80,0x3f0ea50d,0xbf0e250d,0xbf55bf80,0x3e48bec4,0x3f7b3f6d,0xbf7bbf6d,0x3e48bec4,
0x3f7b3f35,0x3e483f35,0xbe48bf35,0x3f7b3f35,0x3f0e3f6d,0xbf55bec4,0x3f553ec4,0x3f0e3f6d,0x3f353f80,0xbf358000,0x3f350000,0x3f353f80,
0xbf35248d,0xbf35bf80,0x3f353f80,0xbf35248d,0xbf35bf80,0x3f35a50d,0xbf35250d,0xbf35bf80,0x3f35a554,0x3f353f80,0xbf35bf80,0x3f35a554,
0xbf0ebf80,0x3f55a50d,0xbf55250d,0xbf0ebf80,0x3f7b3ec4,0x3e483f6d,0xbe48bf6d,0x3f7b3ec4,0xbe483f35,0xbf7bbf35,0x3f7b3f35,0xbe483f35,
0xbf55bf6d,0x3f0ebec4,0xbf0e3ec4,0xbf55bf6d,0x3ec43f80,0xbf6d8000,0x3f6d0000,0x3ec43f80,0xbf6dbf35,0x3ec4bf35,0xbec43f35,0xbf6dbf35,
0x3f6da554,0x3ec43f80,0xbec4bf80,0x3f6da554,0xbec43f35,0xbf6dbf35,0x3f6d3f35,0xbec43f35,0xbe48bf80,0x3f7ba50d,0xbf7b250d,0xbe48bf80,
0x3f0e3f6d,0xbf553ec4,0x3f55bec4,0x3f0e3f6d,0xbf55bf35,0x3f0ebf35,0xbf0e3f35,0xbf55bf35,0x3f7b3ec4,0xbe483f6d,0x3e48bf6d,0x3f7b3ec4,
0x248d3f80,0xbf808000,0x3f800000,0x248d3f80,0xa554bf80,0x3f80a50d,0xbf80250d,0xa554bf80,0x248d3f80,0xbf808000,0x3f800000,0x248d3f80,
0xa554bf80,0x3f80a50d,0xbf80250d,0xa554bf80,0x3e48bf80,0x3f7ba50d,0xbf7b250d,0x3e48bf80,0xbf0e3f6d,0xbf55bec4,0x3f553ec4,0xbf0e3f6d,
0x3f55bf35,0x3f0e3f35,0xbf0ebf35,0x3f55bf35,0xbf7b3ec4,0xbe48bf6d,0x3e483f6d,0xbf7b3ec4,0xbec43f80,0xbf6d8000,0x3f6d0000,0xbec43f80,
0x3f6dbf35,0x3ec43f35,0xbec4bf35,0x3f6dbf35,0xbf6d248d,0x3ec4bf80,0xbec43f80,0xbf6d248d,0x3ec43f35,0xbf6d3f35,0x3f6dbf35,0x3ec43f35,
0x3f0ebf80,0x3f55a50d,0xbf55250d,0x3f0ebf80,0xbf7b3ec4,0x3e48bf6d,0xbe483f6d,0xbf7b3ec4,0x3e483f35,0xbf7b3f35,0x3f7bbf35,0x3e483f35,
0x3f55bf6d,0x3f0e3ec4,0xbf0ebec4,0x3f55bf6d,0xbf353f80,0xbf358000,0x3f350000,0xbf353f80,0x3f35a554,0xbf353f80,0x3f35bf80,0x3f35a554,
0x3f35bf80,0x3f35a50d,0xbf35250d,0x3f35bf80,0xbf35248d,0x3f35bf80,0xbf353f80,0xbf35248d,0x3f55bf80,0x3f0ea50d,0xbf0e250d,0x3f55bf80,
0xbe48bec4,0x3f7bbf6d,0xbf7b3f6d,0xbe48bec4,0xbf7b3f35,0x3e48bf35,0xbe483f35,0xbf7b3f35,0xbf0e3f6d,0xbf553ec4,0x3f55bec4,0xbf0e3f6d,
0xbf6d3f80,0xbec48000,0x3ec40000,0xbf6d3f80,0xbec43f35,0xbf6d3f35,0x3f6dbf35,0xbec43f35,0x3ec4a554,0xbf6d3f80,0x3f6dbf80,0x3ec4a554,
0x3f6dbf35,0xbec43f35,0x3ec4bf35,0x3f6dbf35,0x3f7bbf80,0x3e48a50d,0xbe48250d,0x3f7bbf80,0x3f55bf6d,0x3f0ebec4,0xbf0e3ec4,0x3f55bf6d,
0x3f0ebf35,0x3f55bf35,0xbf553f35,0x3f0ebf35,0x3e48bec4,0x3f7bbf6d,0xbf7b3f6d,0x3e48bec4,0xbf803f80,0xa50d8000,0x250d0000,0xbf803f80,
0xbf803f80,0xa50d8000,0x250d0000,0xbf803f80,0xbf803f80,0xa50d8000,0x250d0000,0xbf803f80,0xbf803f80,0xa50d8000,0x250d0000,0xbf803f80,
0x3f7bbf80,0xbe48a50d,0x3e48250d,0x3f7bbf80,0x3f55bf6d,0xbf0e3ec4,0x3f0ebec4,0x3f55bf6d,0x3f0ebf35,0xbf553f35,0x3f55bf35,0x3f0ebf35,
0x3e48bec4,0xbf7b3f6d,0x3f7bbf6d,0x3e48bec4,0xbf6d3f80,0x3ec48000,0xbec40000,0xbf6d3f80,0xbec43f35,0x3f6dbf35,0xbf6d3f35,0xbec43f35,
0x3ec4248d,0x3f6dbf80,0xbf6d3f80,0x3ec4248d,0x3f6dbf35,0x3ec4bf35,0xbec43f35,0x3f6dbf35,0x3f55bf80,0xbf0ea50d,0x3f0e250d,0x3f55bf80,
0xbe48bec4,0xbf7b3f6d,0x3f7bbf6d,0xbe48bec4,0xbf7b3f35,0xbe483f35,0x3e48bf35,0xbf7b3f35,0xbf0e3f6d,0x3f55bec4,0xbf553ec4,0xbf0e3f6d,
0xbf353f80,0x3f358000,0xbf350000,0xbf353f80,0x3f35248d,0x3f35bf80,0xbf353f80,0x3f35248d,0x3f35bf80,0xbf35a50d,0x3f35250d,0x3f35bf80,
0xbf35a554,0xbf353f80,0x3f35bf80,0xbf35a554,0x3f0ebf80,0xbf55a50d,0x3f55250d,0x3f0ebf80,0xbf7b3ec4,0xbe483f6d,0x3e48bf6d,0xbf7b3ec4,
0x3e483f35,0x3f7bbf35,0xbf7b3f35,0x3e483f35,0x3f55bf6d,0xbf0ebec4,0x3f0e3ec4,0x3f55bf6d,0xbec43f80,0x3f6d8000,0xbf6d0000,0xbec43f80,
0x3f6dbf35,0xbec4bf35,0x3ec43f35,0x3f6dbf35,0xbf6da554,0xbec43f80,0x3ec4bf80,0xbf6da554,0x3ec43f35,0x3f6dbf35,0xbf6d3f35,0x3ec43f35,
0x3e48bf80,0xbf7ba50d,0x3f7b250d,0x3e48bf80,0xbf0e3f6d,0x3f553ec4,0xbf55bec4,0xbf0e3f6d,0x3f55bf35,0xbf0ebf35,0x3f0e3f35,0x3f55bf35,
0xbf7b3ec4,0x3e483f6d,0xbe48bf6d,0xbf7b3ec4,0xa5543f80,0x3f808000,0xbf800000,0xa5543f80,0x248dbf80,0xbf80a50d,0x3f80250d,0x248dbf80,
0xa5543f80,0x3f808000,0xbf800000,0xa5543f80,0x248dbf80,0xbf80a50d,0x3f80250d,0x248dbf80,0xbe48bf80,0xbf7ba50d,0x3f7b250d,0xbe48bf80,
0x3f0e3f6d,0x3f55bec4,0xbf553ec4,0x3f0e3f6d,0xbf55bf35,0xbf0e3f35,0x3f0ebf35,0xbf55bf35,0x3f7b3ec4,0x3e48bf6d,0xbe483f6d,0x3f7b3ec4,
0x3ec43f80,0x3f6d8000,0xbf6d0000,0x3ec43f80,0xbf6dbf35,0xbec43f35,0x3ec4bf35,0xbf6dbf35,0x3f6d248d,0xbec4bf80,0x3ec43f80,0x3f6d248d,
0xbec43f35,0x3f6d3f35,0xbf6dbf35,0xbec43f35,0xbf0ebf80,0xbf55a50d,0x3f55250d,0xbf0ebf80,0x3f7b3ec4,0xbe48bf6d,0x3e483f6d,0x3f7b3ec4,
0xbe483f35,0x3f7b3f35,0xbf7bbf35,0xbe483f35,0xbf55bf6d,0xbf0e3ec4,0x3f0ebec4,0xbf55bf6d,0x3f353f80,0x3f358000,0xbf350000,0x3f353f80,
0xbf35a554,0x3f353f80,0xbf35bf80,0xbf35a554,0xbf35bf80,0xbf35a50d,0x3f35250d,0xbf35bf80,0x3f35248d,0xbf35bf80,0x3f353f80,0x3f35248d,
0xbf55bf80,0xbf0ea50d,0x3f0e250d,0xbf55bf80,0x3e48bec4,0xbf7bbf6d,0x3f7b3f6d,0x3e48bec4,0x3f7b3f35,0xbe48bf35,0x3e483f35,0x3f7b3f35,
0x3f0e3f6d,0x3f553ec4,0xbf55bec4,0x3f0e3f6d,0x3f6d3f80,0x3ec48000,0xbec40000,0x3f6d3f80,0x3ec43f35,0x3f6d3f35,0xbf6dbf35,0x3ec43f35,
0xbec4a554,0x3f6d3f80,0xbf6dbf80,0xbec4a554,0xbf6dbf35,0x3ec43f35,0xbec4bf35,0xbf6dbf35,0xbf7bbf80,0xbe48a50d,0x3e48250d,0xbf7bbf80,
0xbf55bf6d,0xbf0ebec4,0x3f0e3ec4,0xbf55bf6d,0xbf0ebf35,0xbf55bf35,0x3f553f35,0xbf0ebf35,0xbe48bec4,0xbf7bbf6d,0x3f7b3f6d,0xbe48bec4,
0x3f803f80,0x80008000,0,0x3f803f80,0x3f803f80,0x80008000,0,0x3f803f80,0x3f803f80,0x80008000,0,0x3f803f80,
0x3f803f80,0x80008000,0,0x3f803f80,0x3e48a554,0x3f7b3f80,0xbf7bbf80,0x3e48a554,0x3f0e3ec4,0x3f553f6d,0xbf55bf6d,0x3f0e3ec4,
0x3f553f35,0x3f0e3f35,0xbf0ebf35,0x3f553f35,0x3f7b3f6d,0x3e483ec4,0xbe48bec4,0x3f7b3f6d,0xbf6dbf80,0x3ec4a50d,0xbec4250d,0xbf6dbf80,
0xbec4bf35,0x3f6d3f35,0xbf6dbf35,0xbec4bf35,0x3ec4a554,0x3f6d3f80,0xbf6dbf80,0x3ec4a554,0x3f6d3f35,0x3ec43f35,0xbec4bf35,0x3f6d3f35,
0xbf0e248d,0xbf55bf80,0x3f553f80,0xbf0e248d,0xbf7bbf6d,0x3e48bec4,0xbe483ec4,0xbf7bbf6d,0xbe48bf35,0x3f7b3f35,0xbf7bbf35,0xbe48bf35,
0x3f553ec4,0x3f0e3f6d,0xbf0ebf6d,0x3f553ec4,0x3f353f80,0xbf358000,0x3f350000,0x3f353f80,0xbf35248d,0xbf35bf80,0x3f353f80,0xbf35248d,
0xbf35bf80,0x3f35a50d,0xbf35250d,0xbf35bf80,0x3f35a554,0x3f353f80,0xbf35bf80,0x3f35a554,0x3f55a554,0x3f0e3f80,0xbf0ebf80,0x3f55a554,
0x3e483f6d,0xbf7bbec4,0x3f7b3ec4,0x3e483f6d,0xbf7bbf35,0x3e48bf35,0xbe483f35,0xbf7bbf35,0x3f0ebec4,0x3f553f6d,0xbf55bf6d,0x3f0ebec4,
0xbec4bf80,0x3f6da50d,0xbf6d250d,0xbec4bf80,0x3f6d3f35,0xbec43f35,0x3ec4bf35,0x3f6d3f35,0xbf6d248d,0xbec4bf80,0x3ec43f80,0xbf6d248d,
0x3ec4bf35,0x3f6d3f35,0xbf6dbf35,0x3ec4bf35,0xbf7b248d,0xbe48bf80,0x3e483f80,0xbf7b248d,0x3f55bec4,0x3f0e3f6d,0xbf0ebf6d,0x3f55bec4,
0xbf0e3f35,0xbf55bf35,0x3f553f35,0xbf0e3f35,0x3e48bf6d,0x3f7b3ec4,0xbf7bbec4,0x3e48bf6d,0x248d3f80,0xbf808000,0x3f800000,0x248d3f80,
0xa554bf80,0x3f80a50d,0xbf80250d,0xa554bf80,0x248d3f80,0xbf808000,0x3f800000,0x248d3f80,0xa554bf80,0x3f80a50d,0xbf80250d,0xa554bf80,
0x3f7ba554,0xbe483f80,0x3e48bf80,0x3f7ba554,0xbf55bec4,0x3f0ebf6d,0xbf0e3f6d,0xbf55bec4,0x3f0e3f35,0xbf553f35,0x3f55bf35,0x3f0e3f35,
0xbe48bf6d,0x3f7bbec4,0xbf7b3ec4,0xbe48bf6d,0x3ec4bf80,0x3f6da50d,0xbf6d250d,0x3ec4bf80,0xbf6d3f35,0xbec4bf35,0x3ec43f35,0xbf6d3f35,
0x3f6da554,0xbec43f80,0x3ec4bf80,0x3f6da554,0xbec4bf35,0x3f6dbf35,0xbf6d3f35,0xbec4bf35,0xbf55248d,0x3f0ebf80,0xbf0e3f80,0xbf55248d,
0xbe483f6d,0xbf7b3ec4,0x3f7bbec4,0xbe483f6d,0x3f7bbf35,0x3e483f35,0xbe48bf35,0x3f7bbf35,0xbf0ebec4,0x3f55bf6d,0xbf553f6d,0xbf0ebec4,
0xbf353f80,0xbf358000,0x3f350000,0xbf353f80,0x3f35a554,0xbf353f80,0x3f35bf80,0x3f35a554,0x3f35bf80,0x3f35a50d,0xbf35250d,0x3f35bf80,
0xbf35248d,0x3f35bf80,0xbf353f80,0xbf35248d,0x3f0ea554,0xbf553f80,0x3f55bf80,0x3f0ea554,0x3f7bbf6d,0x3e483ec4,0xbe48bec4,0x3f7bbf6d,
0x3e48bf35,0x3f7bbf35,0xbf7b3f35,0x3e48bf35,0xbf553ec4,0x3f0ebf6d,0xbf0e3f6d,0xbf553ec4,0x3f6dbf80,0x3ec4a50d,0xbec4250d,0x3f6dbf80,
0x3ec4bf35,0x3f6dbf35,0xbf6d3f35,0x3ec4bf35,0xbec4248d,0x3f6dbf80,0xbf6d3f80,0xbec4248d,0xbf6d3f35,0x3ec4bf35,0xbec43f35,0xbf6d3f35,
0xbe48248d,0x3f7bbf80,0xbf7b3f80,0xbe48248d,0xbf0e3ec4,0x3f55bf6d,0xbf553f6d,0xbf0e3ec4,0xbf553f35,0x3f0ebf35,0xbf0e3f35,0xbf553f35,
0xbf7b3f6d,0x3e48bec4,0xbe483ec4,0xbf7b3f6d,0xbf803f80,0xa50d8000,0x250d0000,0xbf803f80,0xbf803f80,0xa50d8000,0x250d0000,0xbf803f80,
0xbf803f80,0xa50d8000,0x250d0000,0xbf803f80,0xbf803f80,0xa50d8000,0x250d0000,0xbf803f80,0xbe48a554,0xbf7b3f80,0x3f7bbf80,0xbe48a554,
0xbf0e3ec4,0xbf553f6d,0x3f55bf6d,0xbf0e3ec4,0xbf553f35,0xbf0e3f35,0x3f0ebf35,0xbf553f35,0xbf7b3f6d,0xbe483ec4,0x3e48bec4,0xbf7b3f6d,
0x3f6dbf80,0xbec4a50d,0x3ec4250d,0x3f6dbf80,0x3ec4bf35,0xbf6d3f35,0x3f6dbf35,0x3ec4bf35,0xbec4a554,0xbf6d3f80,0x3f6dbf80,0xbec4a554,
0xbf6d3f35,0xbec43f35,0x3ec4bf35,0xbf6d3f35,0x3f0e248d,0x3f55bf80,0xbf553f80,0x3f0e248d,0x3f7bbf6d,0xbe48bec4,0x3e483ec4,0x3f7bbf6d,
0x3e48bf35,0xbf7b3f35,0x3f7bbf35,0x3e48bf35,0xbf553ec4,0xbf0e3f6d,0x3f0ebf6d,0xbf553ec4,0xbf353f80,0x3f358000,0xbf350000,0xbf353f80,
0x3f35248d,0x3f35bf80,0xbf353f80,0x3f35248d,0x3f35bf80,0xbf35a50d,0x3f35250d,0x3f35bf80,0xbf35a554,0xbf353f80,0x3f35bf80,0xbf35a554,
0xbf55a554,0xbf0e3f80,0x3f0ebf80,0xbf55a554,0xbe483f6d,0x3f7bbec4,0xbf7b3ec4,0xbe483f6d,0x3f7bbf35,0xbe48bf35,0x3e483f35,0x3f7bbf35,
0xbf0ebec4,0xbf553f6d,0x3f55bf6d,0xbf0ebec4,0x3ec4bf80,0xbf6da50d,0x3f6d250d,0x3ec4bf80,0xbf6d3f35,0x3ec43f35,0xbec4bf35,0xbf6d3f35,
0x3f6d248d,0x3ec4bf80,0xbec43f80,0x3f6d248d,0xbec4bf35,0xbf6d3f35,0x3f6dbf35,0xbec4bf35,0x3f7b248d,0x3e48bf80,0xbe483f80,0x3f7b248d,
0xbf55bec4,0xbf0e3f6d,0x3f0ebf6d,0xbf55bec4,0x3f0e3f35,0x3f55bf35,0xbf553f35,0x3f0e3f35,0xbe48bf6d,0xbf7b3ec4,0x3f7bbec4,0xbe48bf6d,
0xa5543f80,0x3f808000,0xbf800000,0xa5543f80,0x248dbf80,0xbf80a50d,0x3f80250d,0x248dbf80,0xa5543f80,0x3f808000,0xbf800000,0xa5543f80,
0x248dbf80,0xbf80a50d,0x3f80250d,0x248dbf80,0xbf7ba554,0x3e483f80,0xbe48bf80,0xbf7ba554,0x3f55bec4,0xbf0ebf6d,0x3f0e3f6d,0x3f55bec4,
0xbf0e3f35,0x3f553f35,0xbf55bf35,0xbf0e3f35,0x3e48bf6d,0xbf7bbec4,0x3f7b3ec4,0x3e48bf6d,0xbec4bf80,0xbf6da50d,0x3f6d250d,0xbec4bf80,
0x3f6d3f35,0x3ec4bf35,0xbec43f35,0x3f6d3f35,0xbf6da554,0x3ec43f80,0xbec4bf80,0xbf6da554,0x3ec4bf35,0xbf6dbf35,0x3f6d3f35,0x3ec4bf35,
0x3f55248d,0xbf0ebf80,0x3f0e3f80,0x3f55248d,0x3e483f6d,0x3f7b3ec4,0xbf7bbec4,0x3e483f6d,0xbf7bbf35,0xbe483f35,0x3e48bf35,0xbf7bbf35,
0x3f0ebec4,0xbf55bf6d,0x3f553f6d,0x3f0ebec4,0x3f353f80,0x3f358000,0xbf350000,0x3f353f80,0xbf35a554,0x3f353f80,0xbf35bf80,0xbf35a554,
0xbf35bf80,0xbf35a50d,0x3f35250d,0xbf35bf80,0x3f35248d,0xbf35bf80,0x3f353f80,0x3f35248d,0xbf0ea554,0x3f553f80,0xbf55bf80,0xbf0ea554,
0xbf7bbf6d,0xbe483ec4,0x3e48bec4,0xbf7bbf6d,0xbe48bf35,0xbf7bbf35,0x3f7b3f35,0xbe48bf35,0x3f553ec4,0xbf0ebf6d,0x3f0e3f6d,0x3f553ec4,
0xbf6dbf80,0xbec4a50d,0x3ec4250d,0xbf6dbf80,0xbec4bf35,0xbf6dbf35,0x3f6d3f35,0xbec4bf35,0x3ec4248d,0xbf6dbf80,0x3f6d3f80,0x3ec4248d,
0x3f6d3f35,0xbec4bf35,0x3ec43f35,0x3f6d3f35,0x3e48248d,0xbf7bbf80,0x3f7b3f80,0x3e48248d,0x3f0e3ec4,0xbf55bf6d,0x3f553f6d,0x3f0e3ec4,
0x3f553f35,0xbf0ebf35,0x3f0e3f35,0x3f553f35,0x3f7b3f6d,0xbe48bec4,0x3e483ec4,0x3f7b3f6d,
};
__device__ __align__(128) const uint32_t T_A32I[2048] = {
0x80003f80,0x3f800000,0x80003f80,0x3f800000,0x80003f80,0x3f800000,0x80003f80,0x3f800000,0x80003f80,0x3f800000,0x80003f80,0x3f800000,
0x80003f80,0x3f800000,0x80003f80,0x3f800000,0x80003f80,0x3f800000,0xbf353f35,0x3f353f35,0xbe483f7b,0x3f7b3e48,0xbf553f0e,0x3f0e3f55,
0xbec43f6d,0x3f6d3ec4,0xbf6d3ec4,0x3ec43f6d,0xbf0e3f55,0x3f553f0e,0xbf7b3e48,0x3e483f7b,0x80003f80,0x3f800000,0xbf80248d,0x248d3f80,
0xbec43f6d,0x3f6d3ec4,0xbf6dbec4,0xbec43f6d,0xbf353f35,0x3f353f35,0xbf35bf35,0xbf353f35,0xbf6d3ec4,0x3ec43f6d,0xbec4bf6d,0xbf6d3ec4,
0x80003f80,0x3f800000,0xbf35bf35,0xbf353f35,0xbf0e3f55,0x3f553f0e,0xbe48bf7b,0xbf7b3e48,0xbf6d3ec4,0x3ec43f6d,0x3ec4bf6d,0xbf6dbec4,
0xbf7bbe48,0xbe483f7b,0x3f55bf0e,0xbf0ebf55,0x80003f80,0x3f800000,0xa50dbf80,0xbf80250d,0xbf353f35,0x3f353f35,0x3f35bf35,0xbf35bf35,
0xbf80248d,0x248d3f80,0x3f80a554,0xa554bf80,0xbf35bf35,0xbf353f35,0x3f353f35,0x3f35bf35,0x80003f80,0x3f800000,0x3f35bf35,0xbf35bf35,
0xbf553f0e,0x3f0e3f55,0x3f7b3e48,0x3e48bf7b,0xbf6dbec4,0xbec43f6d,0x3ec43f6d,0x3f6dbec4,0xbe48bf7b,0xbf7b3e48,0xbf0e3f55,0x3f553f0e,
0x80003f80,0x3f800000,0x3f80a554,0xa554bf80,0xbf6d3ec4,0x3ec43f6d,0x3ec43f6d,0x3f6dbec4,0xbf35bf35,0xbf353f35,0xbf353f35,0x3f353f35,
0x3ec4bf6d,0xbf6dbec4,0xbf6dbec4,0xbec43f6d,0x80003f80,0x3f800000,0x3f353f35,0x3f35bf35,0xbf7b3e48,0x3e483f7b,0xbf0e3f55,0x3f553f0e,
0xbec4bf6d,0xbf6d3ec4,0xbf6dbec4,0xbec43f6d,0x3f55bf0e,0xbf0ebf55,0x3e48bf7b,0xbf7bbe48,0x80003f80,0x3f800000,0x80003f80,0x3f800000,
0xbf80248d,0x248d3f80,0xbf80248d,0x248d3f80,0xa50dbf80,0xbf80250d,0xa50dbf80,0xbf80250d,0x3f80a554,0xa554bf80,0x3f80a554,0xa554bf80,
0x80003f80,0x3f800000,0xbf353f35,0x3f353f35,0xbf7bbe48,0xbe483f7b,0xbf0ebf55,0xbf553f0e,0x3ec4bf6d,0xbf6dbec4,0x3f6dbec4,0xbec4bf6d,
0x3f553f0e,0x3f0ebf55,0x3e483f7b,0x3f7bbe48,0x80003f80,0x3f800000,0xbf80248d,0x248d3f80,0xbf6dbec4,0xbec43f6d,0x3ec4bf6d,0xbf6dbec4,
0x3f35bf35,0xbf35bf35,0x3f353f35,0x3f35bf35,0x3ec43f6d,0x3f6dbec4,0xbf6d3ec4,0x3ec43f6d,0x80003f80,0x3f800000,0xbf35bf35,0xbf353f35,
0xbf55bf0e,0xbf0e3f55,0x3f7bbe48,0xbe48bf7b,0x3f6dbec4,0xbec4bf6d,0xbec43f6d,0x3f6d3ec4,0xbe483f7b,0x3f7b3e48,0xbf0ebf55,0xbf553f0e,
0x80003f80,0x3f800000,0xa50dbf80,0xbf80250d,0xbf35bf35,0xbf353f35,0x3f353f35,0x3f35bf35,0x3f80a554,0xa554bf80,0xbf80248d,0x248d3f80,
0xbf353f35,0x3f353f35,0x3f35bf35,0xbf35bf35,0x80003f80,0x3f800000,0x3f35bf35,0xbf35bf35,0xbf0ebf55,0xbf553f0e,0xbe483f7b,0x3f7b3e48,
0x3f6d3ec4,0x3ec4bf6d,0xbec4bf6d,0xbf6d3ec4,0xbf7b3e48,0x3e483f7b,0x3f553f0e,0x3f0ebf55,0x80003f80,0x3f800000,0x3f80a554,0xa554bf80,
0xbec4bf6d,0xbf6d3ec4,0xbf6d3ec4,0x3ec43f6d,0x3f353f35,0x3f35bf35,0x3f35bf35,0xbf35bf35,0xbf6dbec4,0xbec43f6d,0xbec43f6d,0x3f6d3ec4,
0x80003f80,0x3f800000,0x3f353f35,0x3f35bf35,0xbe48bf7b,0xbf7b3e48,0xbf55bf0e,0xbf0e3f55,0x3ec43f6d,0x3f6dbec4,0x3f6d3ec4,0x3ec4bf6d,
0xbf0ebf55,0xbf553f0e,0xbf7bbe48,0xbe483f7b,0x80003f80,0x3f800000,0x80003f80,0x3f800000,0xa50dbf80,0xbf80250d,0xa50dbf80,0xbf80250d,
0x80003f80,0x3f800000,0x80003f80,0x3f800000,0xa50dbf80,0xbf80250d,0xa50dbf80,0xbf80250d,0x80003f80,0x3f800000,0xbf353f35,0x3f353f35,
0x3e48bf7b,0xbf7bbe48,0x3f55bf0e,0xbf0ebf55,0xbec43f6d,0x3f6d3ec4,0xbf6d3ec4,0x3ec43f6d,0x3f0ebf55,0xbf55bf0e,0x3f7bbe48,0xbe48bf7b,
0x80003f80,0x3f800000,0xbf80248d,0x248d3f80,0x3ec4bf6d,0xbf6dbec4,0x3f6d3ec4,0x3ec4bf6d,0xbf353f35,0x3f353f35,0xbf35bf35,0xbf353f35,
0x3f6dbec4,0xbec4bf6d,0x3ec43f6d,0x3f6dbec4,0x80003f80,0x3f800000,0xbf35bf35,0xbf353f35,0x3f0ebf55,0xbf55bf0e,0x3e483f7b,0x3f7bbe48,
0xbf6d3ec4,0x3ec43f6d,0x3ec4bf6d,0xbf6dbec4,0x3f7b3e48,0x3e48bf7b,0xbf553f0e,0x3f0e3f55,0x80003f80,0x3f800000,0xa50dbf80,0xbf80250d,
0x3f35bf35,0xbf35bf35,0xbf353f35,0x3f353f35,0xbf80248d,0x248d3f80,0x3f80a554,0xa554bf80,0x3f353f35,0x3f35bf35,0xbf35bf35,0xbf353f35,
0x80003f80,0x3f800000,0x3f35bf35,0xbf35bf35,0x3f55bf0e,0xbf0ebf55,0xbf7bbe48,0xbe483f7b,0xbf6dbec4,0xbec43f6d,0x3ec43f6d,0x3f6dbec4,
0x3e483f7b,0x3f7bbe48,0x3f0ebf55,0xbf55bf0e,0x80003f80,0x3f800000,0x3f80a554,0xa554bf80,0x3f6dbec4,0xbec4bf6d,0xbec4bf6d,0xbf6d3ec4,
0xbf35bf35,0xbf353f35,0xbf353f35,0x3f353f35,0xbec43f6d,0x3f6d3ec4,0x3f6d3ec4,0x3ec4bf6d,0x80003f80,0x3f800000,0x3f353f35,0x3f35bf35,
0x3f7bbe48,0xbe48bf7b,0x3f0ebf55,0xbf55bf0e,0xbec4bf6d,0xbf6d3ec4,0xbf6dbec4,0xbec43f6d,0xbf553f0e,0x3f0e3f55,0xbe483f7b,0x3f7b3e48,
0x80003f80,0x3f800000,0x80003f80,0x3f800000,0x3f80a554,0xa554bf80,0x3f80a554,0xa554bf80,0xa50dbf80,0xbf80250d,0xa50dbf80,0xbf80250d,
0xbf80248d,0x248d3f80,0xbf80248d,0x248d3f80,0x80003f80,0x3f800000,0xbf353f35,0x3f353f35,0x3f7b3e48,0x3e48bf7b,0x3f0e3f55,0x3f55bf0e,
0x3ec4bf6d,0xbf6dbec4,0x3f6dbec4,0xbec4bf6d,0xbf55bf0e,0xbf0e3f55,0xbe48bf7b,0xbf7b3e48,0x80003f80,0x3f800000,0xbf80248d,0x248d3f80,
0x3f6d3ec4,0x3ec4bf6d,0xbec43f6d,0x3f6d3ec4,0x3f35bf35,0xbf35bf35,0x3f353f35,0x3f35bf35,0xbec4bf6d,0xbf6d3ec4,0x3f6dbec4,0xbec4bf6d,
0x80003f80,0x3f800000,0xbf35bf35,0xbf353f35,0x3f553f0e,0x3f0ebf55,0xbf7b3e48,0x3e483f7b,0x3f6dbec4,0xbec4bf6d,0xbec43f6d,0x3f6d3ec4,
0x3e48bf7b,0xbf7bbe48,0x3f0e3f55,0x3f55bf0e,0x80003f80,0x3f800000,0xa50dbf80,0xbf80250d,0x3f353f35,0x3f35bf35,0xbf35bf35,0xbf353f35,
0x3f80a554,0xa554bf80,0xbf80248d,0x248d3f80,0x3f35bf35,0xbf35bf35,0xbf353f35,0x3f353f35,0x80003f80,0x3f800000,0x3f35bf35,0xbf35bf35,
0x3f0e3f55,0x3f55bf0e,0x3e48bf7b,0xbf7bbe48,0x3f6d3ec4,0x3ec4bf6d,0xbec4bf6d,0xbf6d3ec4,0x3f7bbe48,0xbe48bf7b,0xbf55bf0e,0xbf0e3f55,
0x80003f80,0x3f800000,0x3f80a554,0xa554bf80,0x3ec43f6d,0x3f6dbec4,0x3f6dbec4,0xbec4bf6d,0x3f353f35,0x3f35bf35,0x3f35bf35,0xbf35bf35,
0x3f6d3ec4,0x3ec4bf6d,0x3ec4bf6d,0xbf6dbec4,0x80003f80,0x3f800000,0x3f353f35,0x3f35bf35,0x3e483f7b,0x3f7bbe48,0x3f553f0e,0x3f0ebf55,
0x3ec43f6d,0x3f6dbec4,0x3f6d3ec4,0x3ec4bf6d,0x3f0e3f55,0x3f55bf0e,0x3f7b3e48,0x3e48bf7b,0x80003f80,0x3f800000,0x80003f80,0x3f800000,
0x80003f80,0x3f800000,0x80003f80,0x3f800000,0x80003f80,0x3f800000,0x80003f80,0x3f800000,0x80003f80,0x3f800000,0x80003f80,0x3f800000,
0xbf80248d,0x248d3f80,0xbf35bf35,0xbf353f35,0xbf7bbe48,0xbe483f7b,0xbf0ebf55,0xbf553f0e,0xbf6dbec4,0xbec43f6d,0xbec4bf6d,0xbf6d3ec4,
0xbf55bf0e,0xbf0e3f55,0xbe48bf7b,0xbf7b3e48,0xa50dbf80,0xbf80250d,0x3f80a554,0xa554bf80,0x3ec4bf6d,0xbf6dbec4,0x3f6d3ec4,0x3ec4bf6d,
0x3f35bf35,0xbf35bf35,0x3f353f35,0x3f35bf35,0x3f6dbec4,0xbec4bf6d,0x3ec43f6d,0x3f6dbec4,0x3f80a554,0xa554bf80,0xbf353f35,0x3f353f35,
0x3f553f0e,0x3f0ebf55,0xbf7b3e48,0x3e483f7b,0x3ec43f6d,0x3f6dbec4,0xbf6dbec4,0xbec43f6d,0xbe483f7b,0x3f7b3e48,0xbf0ebf55,0xbf553f0e,
0x80003f80,0x3f800000,0xa50dbf80,0xbf80250d,0xbf353f35,0x3f353f35,0x3f35bf35,0xbf35bf35,0xbf80248d,0x248d3f80,0x3f80a554,0xa554bf80,
0xbf35bf35,0xbf353f35,0x3f353f35,0x3f35bf35,0xbf80248d,0x248d3f80,0x3f353f35,0x3f35bf35,0xbf0ebf55,0xbf553f0e,0xbe483f7b,0x3f7b3e48,
0x3ec4bf6d,0xbf6dbec4,0xbf6d3ec4,0x3ec43f6d,0x3f7bbe48,0xbe48bf7b,0xbf55bf0e,0xbf0e3f55,0xa50dbf80,0xbf80250d,0xbf80248d,0x248d3f80,
0x3f6dbec4,0xbec4bf6d,0xbec4bf6d,0xbf6d3ec4,0x3f353f35,0x3f35bf35,0x3f35bf35,0xbf35bf35,0xbec43f6d,0x3f6d3ec4,0x3f6d3ec4,0x3ec4bf6d,
0x3f80a554,0xa554bf80,0x3f35bf35,0xbf35bf35,0x3e483f7b,0x3f7bbe48,0x3f553f0e,0x3f0ebf55,0xbf6d3ec4,0x3ec43f6d,0xbec43f6d,0x3f6d3ec4,
0xbf0ebf55,0xbf553f0e,0xbf7bbe48,0xbe483f7b,0x80003f80,0x3f800000,0x80003f80,0x3f800000,0xbf80248d,0x248d3f80,0xbf80248d,0x248d3f80,
0xa50dbf80,0xbf80250d,0xa50dbf80,0xbf80250d,0x3f80a554,0xa554bf80,0x3f80a554,0xa554bf80,0xbf80248d,0x248d3f80,0xbf35bf35,0xbf353f35,
0x3e48bf7b,0xbf7bbe48,0x3f55bf0e,0xbf0ebf55,0x3f6d3ec4,0x3ec4bf6d,0x3ec43f6d,0x3f6dbec4,0xbf0e3f55,0x3f553f0e,0xbf7b3e48,0x3e483f7b,
0xa50dbf80,0xbf80250d,0x3f80a554,0xa554bf80,0x3f6d3ec4,0x3ec4bf6d,0xbec43f6d,0x3f6d3ec4,0xbf353f35,0x3f353f35,0xbf35bf35,0xbf353f35,
0xbec4bf6d,0xbf6d3ec4,0x3f6dbec4,0xbec4bf6d,0x3f80a554,0xa554bf80,0xbf353f35,0x3f353f35,0xbf0e3f55,0x3f553f0e,0xbe48bf7b,0xbf7b3e48,
0xbec4bf6d,0xbf6d3ec4,0x3f6d3ec4,0x3ec4bf6d,0x3f7b3e48,0x3e48bf7b,0xbf553f0e,0x3f0e3f55,0x80003f80,0x3f800000,0xa50dbf80,0xbf80250d,
0xbf35bf35,0xbf353f35,0x3f353f35,0x3f35bf35,0x3f80a554,0xa554bf80,0xbf80248d,0x248d3f80,0xbf353f35,0x3f353f35,0x3f35bf35,0xbf35bf35,
0xbf80248d,0x248d3f80,0x3f353f35,0x3f35bf35,0x3f55bf0e,0xbf0ebf55,0xbf7bbe48,0xbe483f7b,0xbec43f6d,0x3f6d3ec4,0x3f6dbec4,0xbec4bf6d,
0xbe48bf7b,0xbf7b3e48,0xbf0e3f55,0x3f553f0e,0xa50dbf80,0xbf80250d,0xbf80248d,0x248d3f80,0x3ec43f6d,0x3f6dbec4,0x3f6dbec4,0xbec4bf6d,
0xbf35bf35,0xbf353f35,0xbf353f35,0x3f353f35,0x3f6d3ec4,0x3ec4bf6d,0x3ec4bf6d,0xbf6dbec4,0x3f80a554,0xa554bf80,0x3f35bf35,0xbf35bf35,
0xbf7b3e48,0x3e483f7b,0xbf0e3f55,0x3f553f0e,0x3f6dbec4,0xbec4bf6d,0x3ec4bf6d,0xbf6dbec4,0xbf553f0e,0x3f0e3f55,0xbe483f7b,0x3f7b3e48,
0x80003f80,0x3f800000,0x80003f80,0x3f800000,0xa50dbf80,0xbf80250d,0xa50dbf80,0xbf80250d,0x80003f80,0x3f800000,0x80003f80,0x3f800000,
0xa50dbf80,0xbf80250d,0xa50dbf80,0xbf80250d,0xbf80248d,0x248d3f80,0xbf35bf35,0xbf353f35,0x3f7b3e48,0x3e48bf7b,0x3f0e3f55,0x3f55bf0e,
0xbf6dbec4,0xbec43f6d,0xbec4bf6d,0xbf6d3ec4,0x3f553f0e,0x3f0ebf55,0x3e483f7b,0x3f7bbe48,0xa50dbf80,0xbf80250d,0x3f80a554,0xa554bf80,
0xbec43f6d,0x3f6d3ec4,0xbf6dbec4,0xbec43f6d,0x3f35bf35,0xbf35bf35,0x3f353f35,0x3f35bf35,0xbf6d3ec4,0x3ec43f6d,0xbec4bf6d,0xbf6d3ec4,
0x3f80a554,0xa554bf80,0xbf353f35,0x3f353f35,0xbf55bf0e,0xbf0e3f55,0x3f7bbe48,0xbe48bf7b,0x3ec43f6d,0x3f6dbec4,0xbf6dbec4,0xbec43f6d,
0x3e48bf7b,0xbf7bbe48,0x3f0e3f55,0x3f55bf0e,0x80003f80,0x3f800000,0xa50dbf80,0xbf80250d,0x3f35bf35,0xbf35bf35,0xbf353f35,0x3f353f35,
0xbf80248d,0x248d3f80,0x3f80a554,0xa554bf80,0x3f353f35,0x3f35bf35,0xbf35bf35,0xbf353f35,0xbf80248d,0x248d3f80,0x3f353f35,0x3f35bf35,
0x3f0e3f55,0x3f55bf0e,0x3e48bf7b,0xbf7bbe48,0x3ec4bf6d,0xbf6dbec4,0xbf6d3ec4,0x3ec43f6d,0xbf7b3e48,0x3e483f7b,0x3f553f0e,0x3f0ebf55,
0xa50dbf80,0xbf80250d,0xbf80248d,0x248d3f80,0xbf6d3ec4,0x3ec43f6d,0x3ec43f6d,0x3f6dbec4,0x3f353f35,0x3f35bf35,0x3f35bf35,0xbf35bf35,
0x3ec4bf6d,0xbf6dbec4,0xbf6dbec4,0xbec43f6d,0x3f80a554,0xa554bf80,0x3f35bf35,0xbf35bf35,0xbe48bf7b,0xbf7b3e48,0xbf55bf0e,0xbf0e3f55,
0xbf6d3ec4,0x3ec43f6d,0xbec43f6d,0x3f6d3ec4,0x3f0e3f55,0x3f55bf0e,0x3f7b3e48,0x3e48bf7b,0x80003f80,0x3f800000,0x80003f80,0x3f800000,
0x3f80a554,0xa554bf80,0x3f80a554,0xa554bf80,0xa50dbf80,0xbf80250d,0xa50dbf80,0xbf80250d,0xbf80248d,0x248d3f80,0xbf80248d,0x248d3f80,
0xbf80248d,0x248d3f80,0xbf35bf35,0xbf353f35,0xbe483f7b,0x3f7b3e48,0xbf553f0e,0x3f0e3f55,0x3f6d3ec4,0x3ec4bf6d,0x3ec43f6d,0x3f6dbec4,
0x3f0ebf55,0xbf55bf0e,0x3f7bbe48,0xbe48bf7b,0xa50dbf80,0xbf80250d,0x3f80a554,0xa554bf80,0xbf6dbec4,0xbec43f6d,0x3ec4bf6d,0xbf6dbec4,
0xbf353f35,0x3f353f35,0xbf35bf35,0xbf353f35,0x3ec43f6d,0x3f6dbec4,0xbf6d3ec4,0x3ec43f6d,0x3f80a554,0xa554bf80,0xbf353f35,0x3f353f35,
0x3f0ebf55,0xbf55bf0e,0x3e483f7b,0x3f7bbe48,0xbec4bf6d,0xbf6d3ec4,0x3f6d3ec4,0x3ec4bf6d,0xbf7bbe48,0xbe483f7b,0x3f55bf0e,0xbf0ebf55,
0x80003f80,0x3f800000,0xa50dbf80,0xbf80250d,0x3f353f35,0x3f35bf35,0xbf35bf35,0xbf353f35,0x3f80a554,0xa554bf80,0xbf80248d,0x248d3f80,
0x3f35bf35,0xbf35bf35,0xbf353f35,0x3f353f35,0xbf80248d,0x248d3f80,0x3f353f35,0x3f35bf35,0xbf553f0e,0x3f0e3f55,0x3f7b3e48,0x3e48bf7b,
0xbec43f6d,0x3f6d3ec4,0x3f6dbec4,0xbec4bf6d,0x3e483f7b,0x3f7bbe48,0x3f0ebf55,0xbf55bf0e,0xa50dbf80,0xbf80250d,0xbf80248d,0x248d3f80,
0xbec4bf6d,0xbf6d3ec4,0xbf6d3ec4,0x3ec43f6d,0xbf35bf35,0xbf353f35,0xbf353f35,0x3f353f35,0xbf6dbec4,0xbec43f6d,0xbec43f6d,0x3f6d3ec4,
0x3f80a554,0xa554bf80,0x3f35bf35,0xbf35bf35,0x3f7bbe48,0xbe48bf7b,0x3f0ebf55,0xbf55bf0e,0x3f6dbec4,0xbec4bf6d,0x3ec4bf6d,0xbf6dbec4,
0x3f55bf0e,0xbf0ebf55,0x3e48bf7b,0xbf7bbe48,0x80003f80,0x3f800000,0x80003f80,0x3f800000,0x80003f80,0x3f800000,0x80003f80,0x3f800000,
0x80003f80,0x3f800000,0x80003f80,0x3f800000,0x80003f80,0x3f800000,0x80003f80,0x3f800000,0xa50dbf80,0xbf80250d,0x3f35bf35,0xbf35bf35,
0x3e48bf7b,0xbf7bbe48,0x3f55bf0e,0xbf0ebf55,0x3ec4bf6d,0xbf6dbec4,0x3f6dbec4,0xbec4bf6d,0x3f0ebf55,0xbf55bf0e,0x3f7bbe48,0xbe48bf7b,
0x80003f80,0x3f800000,0xbf80248d,0x248d3f80,0xbec43f6d,0x3f6d3ec4,0xbf6dbec4,0xbec43f6d,0xbf353f35,0x3f353f35,0xbf35bf35,0xbf353f35,
0xbf6d3ec4,0x3ec43f6d,0xbec4bf6d,0xbf6d3ec4,0xa50dbf80,0xbf80250d,0x3f353f35,0x3f35bf35,0x3f0ebf55,0xbf55bf0e,0x3e483f7b,0x3f7bbe48,
0x3f6dbec4,0xbec4bf6d,0xbec43f6d,0x3f6d3ec4,0x3f7b3e48,0x3e48bf7b,0xbf553f0e,0x3f0e3f55,0x80003f80,0x3f800000,0xa50dbf80,0xbf80250d,
0xbf353f35,0x3f353f35,0x3f35bf35,0xbf35bf35,0xbf80248d,0x248d3f80,0x3f80a554,0xa554bf80,0xbf35bf35,0xbf353f35,0x3f353f35,0x3f35bf35,
0xa50dbf80,0xbf80250d,0xbf353f35,0x3f353f35,0x3f55bf0e,0xbf0ebf55,0xbf7bbe48,0xbe483f7b,0x3f6d3ec4,0x3ec4bf6d,0xbec4bf6d,0xbf6d3ec4,
0x3e483f7b,0x3f7bbe48,0x3f0ebf55,0xbf55bf0e,0x80003f80,0x3f800000,0x3f80a554,0xa554bf80,0xbf6d3ec4,0x3ec43f6d,0x3ec43f6d,0x3f6dbec4,
0xbf35bf35,0xbf353f35,0xbf353f35,0x3f353f35,0x3ec4bf6d,0xbf6dbec4,0xbf6dbec4,0xbec43f6d,0xa50dbf80,0xbf80250d,0xbf35bf35,0xbf353f35,
0x3f7bbe48,0xbe48bf7b,0x3f0ebf55,0xbf55bf0e,0x3ec43f6d,0x3f6dbec4,0x3f6d3ec4,0x3ec4bf6d,0xbf553f0e,0x3f0e3f55,0xbe483f7b,0x3f7b3e48,
0x80003f80,0x3f800000,0x80003f80,0x3f800000,0xbf80248d,0x248d3f80,0xbf80248d,0x248d3f80,0xa50dbf80,0xbf80250d,0xa50dbf80,0xbf80250d,
0x3f80a554,0xa554bf80,0x3f80a554,0xa554bf80,0xa50dbf80,0xbf80250d,0x3f35bf35,0xbf35bf35,0x3f7b3e48,0x3e48bf7b,0x3f0e3f55,0x3f55bf0e,
0xbec43f6d,0x3f6d3ec4,0xbf6d3ec4,0x3ec43f6d,0xbf55bf0e,0xbf0e3f55,0xbe48bf7b,0xbf7b3e48,0x80003f80,0x3f800000,0xbf80248d,0x248d3f80,
0xbf6dbec4,0xbec43f6d,0x3ec4bf6d,0xbf6dbec4,0x3f35bf35,0xbf35bf35,0x3f353f35,0x3f35bf35,0x3ec43f6d,0x3f6dbec4,0xbf6d3ec4,0x3ec43f6d,
0xa50dbf80,0xbf80250d,0x3f353f35,0x3f35bf35,0x3f553f0e,0x3f0ebf55,0xbf7b3e48,0x3e483f7b,0xbf6d3ec4,0x3ec43f6d,0x3ec4bf6d,0xbf6dbec4,
0x3e48bf7b,0xbf7bbe48,0x3f0e3f55,0x3f55bf0e,0x80003f80,0x3f800000,0xa50dbf80,0xbf80250d,0xbf35bf35,0xbf353f35,0x3f353f35,0x3f35bf35,
0x3f80a554,0xa554bf80,0xbf80248d,0x248d3f80,0xbf353f35,0x3f353f35,0x3f35bf35,0xbf35bf35,0xa50dbf80,0xbf80250d,0xbf353f35,0x3f353f35,
0x3f0e3f55,0x3f55bf0e,0x3e48bf7b,0xbf7bbe48,0xbf6dbec4,0xbec43f6d,0x3ec43f6d,0x3f6dbec4,0x3f7bbe48,0xbe48bf7b,0xbf55bf0e,0xbf0e3f55,
0x80003f80,0x3f800000,0x3f80a554,0xa554bf80,0xbec4bf6d,0xbf6d3ec4,0xbf6d3ec4,0x3ec43f6d,0x3f353f35,0x3f35bf35,0x3f35bf35,0xbf35bf35,
0xbf6dbec4,0xbec43f6d,0xbec43f6d,0x3f6d3ec4,0xa50dbf80,0xbf80250d,0xbf35bf35,0xbf353f35,0x3e483f7b,0x3f7bbe48,0x3f553f0e,0x3f0ebf55,
0xbec4bf6d,0xbf6d3ec4,0xbf6dbec4,0xbec43f6d,0x3f0e3f55,0x3f55bf0e,0x3f7b3e48,0x3e48bf7b,0x80003f80,0x3f800000,0x80003f80,0x3f800000,
0xa50dbf80,0xbf80250d,0xa50dbf80,0xbf80250d,0x80003f80,0x3f800000,0x80003f80,0x3f800000,0xa50dbf80,0xbf80250d,0xa50dbf80,0xbf80250d,
0xa50dbf80,0xbf80250d,0x3f35bf35,0xbf35bf35,0xbe483f7b,0x3f7b3e48,0xbf553f0e,0x3f0e3f55,0x3ec4bf6d,0xbf6dbec4,0x3f6dbec4,0xbec4bf6d,
0xbf0e3f55,0x3f553f0e,0xbf7b3e48,0x3e483f7b,0x80003f80,0x3f800000,0xbf80248d,0x248d3f80,0x3ec4bf6d,0xbf6dbec4,0x3f6d3ec4,0x3ec4bf6d,
0xbf353f35,0x3f353f35,0xbf35bf35,0xbf353f35,0x3f6dbec4,0xbec4bf6d,0x3ec43f6d,0x3f6dbec4,0xa50dbf80,0xbf80250d,0x3f353f35,0x3f35bf35,
0xbf0e3f55,0x3f553f0e,0xbe48bf7b,0xbf7b3e48,0x3f6dbec4,0xbec4bf6d,0xbec43f6d,0x3f6d3ec4,0xbf7bbe48,0xbe483f7b,0x3f55bf0e,0xbf0ebf55,
0x80003f80,0x3f800000,0xa50dbf80,0xbf80250d,0x3f35bf35,0xbf35bf35,0xbf353f35,0x3f353f35,0xbf80248d,0x248d3f80,0x3f80a554,0xa554bf80,
0x3f353f35,0x3f35bf35,0xbf35bf35,0xbf353f35,0xa50dbf80,0xbf80250d,0xbf353f35,0x3f353f35,0xbf553f0e,0x3f0e3f55,0x3f7b3e48,0x3e48bf7b,
0x3f6d3ec4,0x3ec4bf6d,0xbec4bf6d,0xbf6d3ec4,0xbe48bf7b,0xbf7b3e48,0xbf0e3f55,0x3f553f0e,0x80003f80,0x3f800000,0x3f80a554,0xa554bf80,
0x3f6dbec4,0xbec4bf6d,0xbec4bf6d,0xbf6d3ec4,0xbf35bf35,0xbf353f35,0xbf353f35,0x3f353f35,0xbec43f6d,0x3f6d3ec4,0x3f6d3ec4,0x3ec4bf6d,
0xa50dbf80,0xbf80250d,0xbf35bf35,0xbf353f35,0xbf7b3e48,0x3e483f7b,0xbf0e3f55,0x3f553f0e,0x3ec43f6d,0x3f6dbec4,0x3f6d3ec4,0x3ec4bf6d,
0x3f55bf0e,0xbf0ebf55,0x3e48bf7b,0xbf7bbe48,0x80003f80,0x3f800000,0x80003f80,0x3f800000,0x3f80a554,0xa554bf80,0x3f80a554,0xa554bf80,
0xa50dbf80,0xbf80250d,0xa50dbf80,0xbf80250d,0xbf80248d,0x248d3f80,0xbf80248d,0x248d3f80,0xa50dbf80,0xbf80250d,0x3f35bf35,0xbf35bf35,
0xbf7bbe48,0xbe483f7b,0xbf0ebf55,0xbf553f0e,0xbec43f6d,0x3f6d3ec4,0xbf6d3ec4,0x3ec43f6d,0x3f553f0e,0x3f0ebf55,0x3e483f7b,0x3f7bbe48,
0x80003f80,0x3f800000,0xbf80248d,0x248d3f80,0x3f6d3ec4,0x3ec4bf6d,0xbec43f6d,0x3f6d3ec4,0x3f35bf35,0xbf35bf35,0x3f353f35,0x3f35bf35,
0xbec4bf6d,0xbf6d3ec4,0x3f6dbec4,0xbec4bf6d,0xa50dbf80,0xbf80250d,0x3f353f35,0x3f35bf35,0xbf55bf0e,0xbf0e3f55,0x3f7bbe48,0xbe48bf7b,
0xbf6d3ec4,0x3ec43f6d,0x3ec4bf6d,0xbf6dbec4,0xbe483f7b,0x3f7b3e48,0xbf0ebf55,0xbf553f0e,0x80003f80,0x3f800000,0xa50dbf80,0xbf80250d,
0x3f353f35,0x3f35bf35,0xbf35bf35,0xbf353f35,0x3f80a554,0xa554bf80,0xbf80248d,0x248d3f80,0x3f35bf35,0xbf35bf35,0xbf353f35,0x3f353f35,
0xa50dbf80,0xbf80250d,0xbf353f35,0x3f353f35,0xbf0ebf55,0xbf553f0e,0xbe483f7b,0x3f7b3e48,0xbf6dbec4,0xbec43f6d,0x3ec43f6d,0x3f6dbec4,
0xbf7b3e48,0x3e483f7b,0x3f553f0e,0x3f0ebf55,0x80003f80,0x3f800000,0x3f80a554,0xa554bf80,0x3ec43f6d,0x3f6dbec4,0x3f6dbec4,0xbec4bf6d,
0x3f353f35,0x3f35bf35,0x3f35bf35,0xbf35bf35,0x3f6d3ec4,0x3ec4bf6d,0x3ec4bf6d,0xbf6dbec4,0xa50dbf80,0xbf80250d,0xbf35bf35,0xbf353f35,
0xbe48bf7b,0xbf7b3e48,0xbf55bf0e,0xbf0e3f55,0xbec4bf6d,0xbf6d3ec4,0xbf6dbec4,0xbec43f6d,0xbf0ebf55,0xbf553f0e,0xbf7bbe48,0xbe483f7b,
0x80003f80,0x3f800000,0x80003f80,0x3f800000,0x80003f80,0x3f800000,0x80003f80,0x3f800000,0x80003f80,0x3f800000,0x80003f80,0x3f800000,
0x80003f80,0x3f800000,0x80003f80,0x3f800000,0x3f80a554,0xa554bf80,0x3f353f35,0x3f35bf35,0x3f7b3e48,0x3e48bf7b,0x3f0e3f55,0x3f55bf0e,
0x3f6d3ec4,0x3ec4bf6d,0x3ec43f6d,0x3f6dbec4,0x3f553f0e,0x3f0ebf55,0x3e483f7b,0x3f7bbe48,0xa50dbf80,0xbf80250d,0x3f80a554,0xa554bf80,
0x3ec4bf6d,0xbf6dbec4,0x3f6d3ec4,0x3ec4bf6d,0x3f35bf35,0xbf35bf35,0x3f353f35,0x3f35bf35,0x3f6dbec4,0xbec4bf6d,0x3ec43f6d,0x3f6dbec4,
0xbf80248d,0x248d3f80,0x3f35bf35,0xbf35bf35,0xbf55bf0e,0xbf0e3f55,0x3f7bbe48,0xbe48bf7b,0xbec4bf6d,0xbf6d3ec4,0x3f6d3ec4,0x3ec4bf6d,
0x3e48bf7b,0xbf7bbe48,0x3f0e3f55,0x3f55bf0e,0x80003f80,0x3f800000,0xa50dbf80,0xbf80250d,0xbf353f35,0x3f353f35,0x3f35bf35,0xbf35bf35,
0xbf80248d,0x248d3f80,0x3f80a554,0xa554bf80,0xbf35bf35,0xbf353f35,0x3f353f35,0x3f35bf35,0x3f80a554,0xa554bf80,0xbf35bf35,0xbf353f35,
0x3f0e3f55,0x3f55bf0e,0x3e48bf7b,0xbf7bbe48,0xbec43f6d,0x3f6d3ec4,0x3f6dbec4,0xbec4bf6d,0xbf7b3e48,0x3e483f7b,0x3f553f0e,0x3f0ebf55,
0xa50dbf80,0xbf80250d,0xbf80248d,0x248d3f80,0x3f6dbec4,0xbec4bf6d,0xbec4bf6d,0xbf6d3ec4,0x3f353f35,0x3f35bf35,0x3f35bf35,0xbf35bf35,
0xbec43f6d,0x3f6d3ec4,0x3f6d3ec4,0x3ec4bf6d,0xbf80248d,0x248d3f80,0xbf353f35,0x3f353f35,0xbe48bf7b,0xbf7b3e48,0xbf55bf0e,0xbf0e3f55,
0x3f6dbec4,0xbec4bf6d,0x3ec4bf6d,0xbf6dbec4,0x3f0e3f55,0x3f55bf0e,0x3f7b3e48,0x3e48bf7b,0x80003f80,0x3f800000,0x80003f80,0x3f800000,
0xbf80248d,0x248d3f80,0xbf80248d,0x248d3f80,0xa50dbf80,0xbf80250d,0xa50dbf80,0xbf80250d,0x3f80a554,0xa554bf80,0x3f80a554,0xa554bf80,
0x3f80a554,0xa554bf80,0x3f353f35,0x3f35bf35,0xbe483f7b,0x3f7b3e48,0xbf553f0e,0x3f0e3f55,0xbf6dbec4,0xbec43f6d,0xbec4bf6d,0xbf6d3ec4,
0x3f0ebf55,0xbf55bf0e,0x3f7bbe48,0xbe48bf7b,0xa50dbf80,0xbf80250d,0x3f80a554,0xa554bf80,0x3f6d3ec4,0x3ec4bf6d,0xbec43f6d,0x3f6d3ec4,
0xbf353f35,0x3f353f35,0xbf35bf35,0xbf353f35,0xbec4bf6d,0xbf6d3ec4,0x3f6dbec4,0xbec4bf6d,0xbf80248d,0x248d3f80,0x3f35bf35,0xbf35bf35,
0x3f0ebf55,0xbf55bf0e,0x3e483f7b,0x3f7bbe48,0x3ec43f6d,0x3f6dbec4,0xbf6dbec4,0xbec43f6d,0xbf7bbe48,0xbe483f7b,0x3f55bf0e,0xbf0ebf55,
0x80003f80,0x3f800000,0xa50dbf80,0xbf80250d,0xbf35bf35,0xbf353f35,0x3f353f35,0x3f35bf35,0x3f80a554,0xa554bf80,0xbf80248d,0x248d3f80,
0xbf353f35,0x3f353f35,0x3f35bf35,0xbf35bf35,0x3f80a554,0xa554bf80,0xbf35bf35,0xbf353f35,0xbf553f0e,0x3f0e3f55,0x3f7b3e48,0x3e48bf7b,
0x3ec4bf6d,0xbf6dbec4,0xbf6d3ec4,0x3ec43f6d,0x3e483f7b,0x3f7bbe48,0x3f0ebf55,0xbf55bf0e,0xa50dbf80,0xbf80250d,0xbf80248d,0x248d3f80,
0x3ec43f6d,0x3f6dbec4,0x3f6dbec4,0xbec4bf6d,0xbf35bf35,0xbf353f35,0xbf353f35,0x3f353f35,0x3f6d3ec4,0x3ec4bf6d,0x3ec4bf6d,0xbf6dbec4,
0xbf80248d,0x248d3f80,0xbf353f35,0x3f353f35,0x3f7bbe48,0xbe48bf7b,0x3f0ebf55,0xbf55bf0e,0xbf6d3ec4,0x3ec43f6d,0xbec43f6d,0x3f6d3ec4,
0x3f55bf0e,0xbf0ebf55,0x3e48bf7b,0xbf7bbe48,0x80003f80,0x3f800000,0x80003f80,0x3f800000,0xa50dbf80,0xbf80250d,0xa50dbf80,0xbf80250d,
0x80003f80,0x3f800000,0x80003f80,0x3f800000,0xa50dbf80,0xbf80250d,0xa50dbf80,0xbf80250d,0x3f80a554,0xa554bf80,0x3f353f35,0x3f35bf35,
0xbf7bbe48,0xbe483f7b,0xbf0ebf55,0xbf553f0e,0x3f6d3ec4,0x3ec4bf6d,0x3ec43f6d,0x3f6dbec4,0xbf55bf0e,0xbf0e3f55,0xbe48bf7b,0xbf7b3e48,
0xa50dbf80,0xbf80250d,0x3f80a554,0xa554bf80,0xbec43f6d,0x3f6d3ec4,0xbf6dbec4,0xbec43f6d,0x3f35bf35,0xbf35bf35,0x3f353f35,0x3f35bf35,
0xbf6d3ec4,0x3ec43f6d,0xbec4bf6d,0xbf6d3ec4,0xbf80248d,0x248d3f80,0x3f35bf35,0xbf35bf35,0x3f553f0e,0x3f0ebf55,0xbf7b3e48,0x3e483f7b,
0xbec4bf6d,0xbf6d3ec4,0x3f6d3ec4,0x3ec4bf6d,0xbe483f7b,0x3f7b3e48,0xbf0ebf55,0xbf553f0e,0x80003f80,0x3f800000,0xa50dbf80,0xbf80250d,
0x3f35bf35,0xbf35bf35,0xbf353f35,0x3f353f35,0xbf80248d,0x248d3f80,0x3f80a554,0xa554bf80,0x3f353f35,0x3f35bf35,0xbf35bf35,0xbf353f35,
0x3f80a554,0xa554bf80,0xbf35bf35,0xbf353f35,0xbf0ebf55,0xbf553f0e,0xbe483f7b,0x3f7b3e48,0xbec43f6d,0x3f6d3ec4,0x3f6dbec4,0xbec4bf6d,
0x3f7bbe48,0xbe48bf7b,0xbf55bf0e,0xbf0e3f55,0xa50dbf80,0xbf80250d,0xbf80248d,0x248d3f80,0xbf6d3ec4,0x3ec43f6d,0x3ec43f6d,0x3f6dbec4,
0x3f353f35,0x3f35bf35,0x3f35bf35,0xbf35bf35,0x3ec4bf6d,0xbf6dbec4,0xbf6dbec4,0xbec43f6d,0xbf80248d,0x248d3f80,0xbf353f35,0x3f353f35,
0x3e483f7b,0x3f7bbe48,0x3f553f0e,0x3f0ebf55,0x3f6dbec4,0xbec4bf6d,0x3ec4bf6d,0xbf6dbec4,0xbf0ebf55,0xbf553f0e,0xbf7bbe48,0xbe483f7b,
0x80003f80,0x3f800000,0x80003f80,0x3f800000,0x3f80a554,0xa554bf80,0x3f80a554,0xa554bf80,0xa50dbf80,0xbf80250d,0xa50dbf80,0xbf80250d,
0xbf80248d,0x248d3f80,0xbf80248d,0x248d3f80,0x3f80a554,0xa554bf80,0x3f353f35,0x3f35bf35,0x3e48bf7b,0xbf7bbe48,0x3f55bf0e,0xbf0ebf55,
0xbf6dbec4,0xbec43f6d,0xbec4bf6d,0xbf6d3ec4,0xbf0e3f55,0x3f553f0e,0xbf7b3e48,0x3e483f7b,0xa50dbf80,0xbf80250d,0x3f80a554,0xa554bf80,
0xbf6dbec4,0xbec43f6d,0x3ec4bf6d,0xbf6dbec4,0xbf353f35,0x3f353f35,0xbf35bf35,0xbf353f35,0x3ec43f6d,0x3f6dbec4,0xbf6d3ec4,0x3ec43f6d,
0xbf80248d,0x248d3f80,0x3f35bf35,0xbf35bf35,0xbf0e3f55,0x3f553f0e,0xbe48bf7b,0xbf7b3e48,0x3ec43f6d,0x3f6dbec4,0xbf6dbec4,0xbec43f6d,
0x3f7b3e48,0x3e48bf7b,0xbf553f0e,0x3f0e3f55,0x80003f80,0x3f800000,0xa50dbf80,0xbf80250d,0x3f353f35,0x3f35bf35,0xbf35bf35,0xbf353f35,
0x3f80a554,0xa554bf80,0xbf80248d,0x248d3f80,0x3f35bf35,0xbf35bf35,0xbf353f35,0x3f353f35,0x3f80a554,0xa554bf80,0xbf35bf35,0xbf353f35,
0x3f55bf0e,0xbf0ebf55,0xbf7bbe48,0xbe483f7b,0x3ec4bf6d,0xbf6dbec4,0xbf6d3ec4,0x3ec43f6d,0xbe48bf7b,0xbf7b3e48,0xbf0e3f55,0x3f553f0e,
0xa50dbf80,0xbf80250d,0xbf80248d,0x248d3f80,0xbec4bf6d,0xbf6d3ec4,0xbf6d3ec4,0x3ec43f6d,0xbf35bf35,0xbf353f35,0xbf353f35,0x3f353f35,
0xbf6dbec4,0xbec43f6d,0xbec43f6d,0x3f6d3ec4,0xbf80248d,0x248d3f80,0xbf353f35,0x3f353f35,0xbf7b3e48,0x3e483f7b,0xbf0e3f55,0x3f553f0e,
0xbf6d3ec4,0x3ec43f6d,0xbec43f6d,0x3f6d3ec4,0xbf553f0e,0x3f0e3f55,0xbe483f7b,0x3f7b3e48,
};
__device__ __align__(128) const uint32_t T_TW640[2560] = {
0x3f800000,0,0x3f800000,0,0x3f800000,0,0x3f800000,0,0x3f800000,0,0x3f800000,0,
0x3f800000,0,0x3f800000,0,0x3f800000,0,0x3f7ffcd7,0x3c20d8d2,0x3f7ff35e,0x3ca0d6d6,0x3f7fe394,0x3cf13d4c,
0x3f7fcd79,0x3d20cee7,0x3f7fb10f,0x3d48fb30,0x3f7f8e56,0x3d712283,0x3f7f654e,0x3d8ca1f2,0x3f800000,0,0x3f7ff35e,0x3ca0d6d6,
0x3f7fcd79,0x3d20cee7,0x3f7f8e56,0x3d712283,0x3f7f35f9,0x3da0af2a,0x3f7ec46d,0x3dc8bd36,0x3f7e39bc,0x3df0b772,0x3f7d95f4,0x3e0c4cf7,
0x3f800000,0,0x3f7fe394,0x3cf13d4c,0x3f7f8e56,0x3d712283,0x3f7f0059,0x3db4b86a,0x3f7e39bc,0x3df0b772,0x3f7d3aac,0x3e164083,
0x3f7c0361,0x3e3403f1,0x3f7a9421,0x3e519f65,0x3f800000,0,0x3f7fcd79,0x3d20cee7,0x3f7f35f9,0x3da0af2a,0x3f7e39bc,0x3df0b772,
0x3f7cd925,0x3e20305b,0x3f7b14be,0x3e47c5c2,0x3f78ed3c,0x3e6f0c4d,0x3f766377,0x3e8afa3e,0x3f800000,0,0x3f7fb10f,0x3d48fb30,
0x3f7ec46d,0x3dc8bd36,0x3f7d3aac,0x3e164083,0x3f7b14be,0x3e47c5c2,0x3f7853f8,0x3e78cfcc,0x3f74fa0b,0x3e94a031,0x3f710908,0x3eac7cd4,
0x3f800000,0,0x3f7f8e56,0x3d712283,0x3f7e39bc,0x3df0b772,0x3f7c0361,0x3e3403f1,0x3f78ed3c,0x3e6f0c4d,0x3f74fa0b,0x3e94a031,
0x3f702d4f,0x3eb13641,0x3f6a8b4b,0x3ecd2ef3,0x3f800000,0,0x3f7f654e,0x3d8ca1f2,0x3f7d95f4,0x3e0c4cf7,0x3f7a9421,0x3e519f65,
0x3f766377,0x3e8afa3e,0x3f710908,0x3eac7cd4,0x3f6a8b4b,0x3ecd2ef3,0x3f62f219,0x3eece91a,0x3f800000,0,0x3f7f35f9,0x3da0af2a,
0x3f7cd925,0x3e20305b,0x3f78ed3c,0x3e6f0c4d,0x3f737871,0x3e9e377a,0x3f6c835e,0x3ec3ef15,0x3f641901,0x3ee87171,0x3f5a46a0,0x3f05c277,
0x3f800000,0,0x3f7f0059,0x3db4b86a,0x3f7c0361,0x3e3403f1,0x3f770f11,0x3e862210,0x3f702d4f,0x3eb13641,0x3f676bd8,0x3edae880,
0x3f5cdc29,0x3f0172c3,0x3f50935b,0x3f146eba,0x3f800000,0,0x3f7ec46d,0x3dc8bd36,0x3f7b14be,0x3e47c5c2,0x3f74fa0b,0x3e94a031,
0x3f6c835e,0x3ec3ef15,0x3f61c598,0x3ef15aea,0x3f54db31,0x3f0e39da,0x3f45e403,0x3f226799,0x3f800000,0,0x3f7e8238,0x3ddcbd0d,
0x3f7a0d54,0x3e5b73dc,0x3f72ae9e,0x3ea2fd52,0x3f687c12,0x3ed65a92,0x3f5b941a,0x3f039c3d,0x3f4c1d35,0x3f1a82a4,0x3f3a4582,0x3f2f9c32,
0x3f800000,0,0x3f7e39bc,0x3df0b772,0x3f78ed3c,0x3e6f0c4d,0x3f702d4f,0x3eb13641,0x3f641901,0x3ee87171,0x3f54db31,0x3f0e39da,
0x3f42a9f7,0x3f26423a,0x3f2dc5e3,0x3f3bfc8f,0x3f800000,0,0x3f7deafa,0x3e0255f4,0x3f77b493,0x3e814693,0x3f6d76aa,0x3ebf47d7,
0x3f5f5be6,0x3efa2c90,0x3f4d9f02,0x3f187fc0,0x3f3889dc,0x3f316e2c,0x3f207440,0x3f4779bc,0x3f800000,0,0x3f7d95f4,0x3e0c4cf7,
0x3f766377,0x3e8afa3e,0x3f6a8b4b,0x3ecd2ef3,0x3f5a46a0,0x3f05c277,0x3f45e403,0x3f226799,0x3f2dc5e3,0x3f3bfc8f,0x3f1260b2,0x3f5205d4,
0x3f800000,0,0x3f7d3aac,0x3e164083,0x3f74fa0b,0x3e94a031,0x3f676bd8,0x3edae880,0x3f54db31,0x3f0e39da,0x3f3daef9,0x3f2beb4a,
0x3f226799,0x3f45e403,0x3f039c3d,0x3f5b941a,0x3f800000,0,0x3f7cd925,0x3e20305b,0x3f737871,0x3e9e377a,0x3f641901,0x3ee87171,
0x3f4f1bbd,0x3f167918,0x3f3504f3,0x3f3504f3,0x3f167918,0x3f4f1bbd,0x3ee87171,0x3f641901,0x3f800000,0,0x3f7c7160,0x3e2a1c3f,
0x3f71decf,0x3ea7bf25,0x3f609384,0x3ef5c6c5,0x3f490a88,0x3f1e7cf1,0x3f2beb4a,0x3f3daef9,0x3f0a04f8,0x3f579b8c,0x3ec8917e,0x3f6b8a3d,
0x3f800000,0,0x3f7c0361,0x3e3403f1,0x3f702d4f,0x3eb13641,0x3f5cdc29,0x3f0172c3,0x3f42a9f7,0x3f26423a,0x3f226799,0x3f45e403,
0x3efa2c90,0x3f5f5be6,0x3ea7bf25,0x3f71decf,0x3f800000,0,0x3f7b8f2a,0x3e3de731,0x3f6e641a,0x3eba9be1,0x3f58f3c4,0x3f07e565,
0x3f3bfc8f,0x3f2dc5e3,0x3f187fc0,0x3f4d9f02,0x3edf7108,0x3f6655e7,0x3e862210,0x3f770f11,0x3f800000,0,0x3f7b14be,0x3e47c5c2,
0x3f6c835e,0x3ec3ef15,0x3f54db31,0x3f0e39da,0x3f3504f3,0x3f3504f3,0x3f0e39da,0x3f54db31,0x3ec3ef15,0x3f6c835e,0x3e47c5c2,0x3f7b14be,
0x3f800000,0,0x3f7a9421,0x3e519f65,0x3f6a8b4b,0x3ecd2ef3,0x3f50935b,0x3f146eba,0x3f2dc5e3,0x3f3bfc8f,0x3f039c3d,0x3f5b941a,
0x3ea7bf25,0x3f71decf,0x3e0255f4,0x3f7deafa,0x3f800000,0,0x3f7a0d54,0x3e5b73dc,0x3f687c12,0x3ed65a92,0x3f4c1d35,0x3f1a82a4,
0x3f26423a,0x3f42a9f7,0x3ef15aea,0x3f61c598,0x3e8afa3e,0x3f766377,0x3d712283,0x3f7f8e56,0x3f800000,0,0x3f79805c,0x3e6542e9,
0x3f6655e7,0x3edf7108,0x3f4779bc,0x3f207440,0x3f1e7cf1,0x3f490a88,0x3edae880,0x3f676bd8,0x3e5b73dc,0x3f7a0d54,0xbc20d8d2,0x3f7ffcd7,
0x3f800000,0,0x3f78ed3c,0x3e6f0c4d,0x3f641901,0x3ee87171,0x3f42a9f7,0x3f26423a,0x3f167918,0x3f4f1bbd,0x3ec3ef15,0x3f6c835e,
0x3e20305b,0x3f7cd925,0xbda0af2a,0x3f7f35f9,0x3f800000,0,0x3f7853f8,0x3e78cfcc,0x3f61c598,0x3ef15aea,0x3f3daef9,0x3f2beb4a,
0x3f0e39da,0x3f54db31,0x3eac7cd4,0x3f710908,0x3dc8bd36,0x3f7ec46d,0xbe164083,0x3f7d3aac,0x3f800000,0,0x3f77b493,0x3e814693,
0x3f5f5be6,0x3efa2c90,0x3f3889dc,0x3f316e2c,0x3f05c277,0x3f5a46a0,0x3e94a031,0x3f74fa0b,0x3d20cee7,0x3f7fcd79,0xbe5b73dc,0x3f7a0d54,
0x3f800000,0,0x3f770f11,0x3e862210,0x3f5cdc29,0x3f0172c3,0x3f333bc6,0x3f36c9a9,0x3efa2c90,0x3f5f5be6,0x3e78cfcc,0x3f7853f8,
0xbca0d6d6,0x3f7ff35e,0xbe8fcefe,0x3f75b1c9,0x3f800000,0,0x3f766377,0x3e8afa3e,0x3f5a46a0,0x3f05c277,0x3f2dc5e3,0x3f3bfc8f,
0x3ee87171,0x3f641901,0x3e47c5c2,0x3f7b14be,0xbda0af2a,0x3f7f35f9,0xbeb13641,0x3f702d4f,0x3f800000,0,0x3f75b1c9,0x3e8fcefe,
0x3f579b8c,0x3f0a04f8,0x3f28296a,0x3f4105b8,0x3ed65a92,0x3f687c12,0x3e164083,0x3f7d3aac,0xbe0c4cf7,0x3f7d95f4,0xbed1c759,0x3f698690,
0x3f800000,0,0x3f74fa0b,0x3e94a031,0x3f54db31,0x3f0e39da,0x3f226799,0x3f45e403,0x3ec3ef15,0x3f6c835e,0x3dc8bd36,0x3f7ec46d,
0xbe47c5c2,0x3f7b14be,0xbef15aea,0x3f61c598,0x3f800000,0,0x3f743c41,0x3e996dba,0x3f5205d4,0x3f1260b2,0x3f1c81b9,0x3f4a965e,
0x3eb13641,0x3f702d4f,0x3d48fb30,0x3f7fb10f,0xbe814693,0x3f77b493,0xbf07e565,0x3f58f3c4,0x3f800000,0,0x3f800000,0,
0x3f800000,0,0x3f800000,0,0x3f800000,0,0x3f800000,0,0x3f800000,0,0x3f800000,0,
0x3f7f35f9,0x3da0af2a,0x3f7f0059,0x3db4b86a,0x3f7ec46d,0x3dc8bd36,0x3f7e8238,0x3ddcbd0d,0x3f7e39bc,0x3df0b772,0x3f7deafa,0x3e0255f4,
0x3f7d95f4,0x3e0c4cf7,0x3f7d3aac,0x3e164083,0x3f7cd925,0x3e20305b,0x3f7c0361,0x3e3403f1,0x3f7b14be,0x3e47c5c2,0x3f7a0d54,0x3e5b73dc,
0x3f78ed3c,0x3e6f0c4d,0x3f77b493,0x3e814693,0x3f766377,0x3e8afa3e,0x3f74fa0b,0x3e94a031,0x3f78ed3c,0x3e6f0c4d,0x3f770f11,0x3e862210,
0x3f74fa0b,0x3e94a031,0x3f72ae9e,0x3ea2fd52,0x3f702d4f,0x3eb13641,0x3f6d76aa,0x3ebf47d7,0x3f6a8b4b,0x3ecd2ef3,0x3f676bd8,0x3edae880,
0x3f737871,0x3e9e377a,0x3f702d4f,0x3eb13641,0x3f6c835e,0x3ec3ef15,0x3f687c12,0x3ed65a92,0x3f641901,0x3ee87171,0x3f5f5be6,0x3efa2c90,
0x3f5a46a0,0x3f05c277,0x3f54db31,0x3f0e39da,0x3f6c835e,0x3ec3ef15,0x3f676bd8,0x3edae880,0x3f61c598,0x3ef15aea,0x3f5b941a,0x3f039c3d,
0x3f54db31,0x3f0e39da,0x3f4d9f02,0x3f187fc0,0x3f45e403,0x3f226799,0x3f3daef9,0x3f2beb4a,0x3f641901,0x3ee87171,0x3f5cdc29,0x3f0172c3,
0x3f54db31,0x3f0e39da,0x3f4c1d35,0x3f1a82a4,0x3f42a9f7,0x3f26423a,0x3f3889dc,0x3f316e2c,0x3f2dc5e3,0x3f3bfc8f,0x3f226799,0x3f45e403,
0x3f5a46a0,0x3f05c277,0x3f50935b,0x3f146eba,0x3f45e403,0x3f226799,0x3f3a4582,0x3f2f9c32,0x3f2dc5e3,0x3f3bfc8f,0x3f207440,0x3f4779bc,
0x3f1260b2,0x3f5205d4,0x3f039c3d,0x3f5b941a,0x3f4f1bbd,0x3f167918,0x3f42a9f7,0x3f26423a,0x3f3504f3,0x3f3504f3,0x3f26423a,0x3f42a9f7,
0x3f167918,0x3f4f1bbd,0x3f05c277,0x3f5a46a0,0x3ee87171,0x3f641901,0x3ec3ef15,0x3f6c835e,0x3f42a9f7,0x3f26423a,0x3f333bc6,0x3f36c9a9,
0x3f226799,0x3f45e403,0x3f104f0e,0x3f53731f,0x3efa2c90,0x3f5f5be6,0x3ed1c759,0x3f698690,0x3ea7bf25,0x3f71decf,0x3e78cfcc,0x3f7853f8,
0x3f3504f3,0x3f3504f3,0x3f226799,0x3f45e403,0x3f0e39da,0x3f54db31,0x3ef15aea,0x3f61c598,0x3ec3ef15,0x3f6c835e,0x3e94a031,0x3f74fa0b,
0x3e47c5c2,0x3f7b14be,0x3dc8bd36,0x3f7ec46d,0x3f26423a,0x3f42a9f7,0x3f104f0e,0x3f53731f,0x3ef15aea,0x3f61c598,0x3ebf47d7,0x3f6d76aa,
0x3e8afa3e,0x3f766377,0x3e2a1c3f,0x3f7c7160,0x3d712283,0x3f7f8e56,0xbd48fb30,0x3f7fb10f,0x3f167918,0x3f4f1bbd,0x3efa2c90,0x3f5f5be6,
0x3ec3ef15,0x3f6c835e,0x3e8afa3e,0x3f766377,0x3e20305b,0x3f7cd925,0x3d20cee7,0x3f7fcd79,0xbda0af2a,0x3f7f35f9,0xbe47c5c2,0x3f7b14be,
0x3f05c277,0x3f5a46a0,0x3ed1c759,0x3f698690,0x3e94a031,0x3f74fa0b,0x3e2a1c3f,0x3f7c7160,0x3d20cee7,0x3f7fcd79,0xbdb4b86a,0x3f7f0059,
0xbe5b73dc,0x3f7a0d54,0xbeac7cd4,0x3f710908,0x3ee87171,0x3f641901,0x3ea7bf25,0x3f71decf,0x3e47c5c2,0x3f7b14be,0x3d712283,0x3f7f8e56,
0xbda0af2a,0x3f7f35f9,0xbe5b73dc,0x3f7a0d54,0xbeb13641,0x3f702d4f,0xbef15aea,0x3f61c598,0x3ec3ef15,0x3f6c835e,0x3e78cfcc,0x3f7853f8,
0x3dc8bd36,0x3f7ec46d,0xbd48fb30,0x3f7fb10f,0xbe47c5c2,0x3f7b14be,0xbeac7cd4,0x3f710908,0xbef15aea,0x3f61c598,0xbf187fc0,0x3f4d9f02,
0x3e9e377a,0x3f737871,0x3e20305b,0x3f7cd925,0x248d3132,0x3f800000,0xbe20305b,0x3f7cd925,0xbe9e377a,0x3f737871,0xbee87171,0x3f641901,
0xbf167918,0x3f4f1bbd,0xbf3504f3,0x3f3504f3,0x3e6f0c4d,0x3f78ed3c,0x3d8ca1f2,0x3f7f654e,0xbdc8bd36,0x3f7ec46d,0xbe862210,0x3f770f11,
0xbed65a92,0x3f687c12,0xbf104f0e,0x3f53731f,0xbf316e2c,0x3f3889dc,0xbf4d9f02,0x3f187fc0,0x3e20305b,0x3f7cd925,0xbca0d6d6,0x3f7ff35e,
0xbe47c5c2,0x3f7b14be,0xbeba9be1,0x3f6e641a,0xbf05c277,0x3f5a46a0,0xbf2a0c73,0x3f3f5cb5,0xbf490a88,0x3f1e7cf1,0xbf61c598,0x3ef15aea,
0x3da0af2a,0x3f7f35f9,0xbddcbd0d,0x3f7e8238,0xbe94a031,0x3f74fa0b,0xbeece91a,0x3f62f219,0xbf1e7cf1,0x3f490a88,0xbf4105b8,0x3f28296a,
0xbf5cdc29,0x3f0172c3,0xbf710908,0x3eac7cd4,0x248d3132,0x3f800000,0xbe47c5c2,0x3f7b14be,0xbec3ef15,0x3f6c835e,0xbf0e39da,0x3f54db31,
0xbf3504f3,0x3f3504f3,0xbf54db31,0x3f0e39da,0xbf6c835e,0x3ec3ef15,0xbf7b14be,0x3e47c5c2,0xbda0af2a,0x3f7f35f9,0xbe8fcefe,0x3f75b1c9,
0xbef15aea,0x3f61c598,0xbf2456f1,0x3f444969,0xbf490a88,0x3f1e7cf1,0xbf653a48,0x3ee3f40d,0xbf77b493,0x3e814693,0xbf7fb10f,0x3d48fb30,
0xbe20305b,0x3f7cd925,0xbeba9be1,0x3f6e641a,0xbf0e39da,0x3f54db31,0xbf3889dc,0x3f316e2c,0xbf5a46a0,0x3f05c277,0xbf71decf,0x3ea7bf25,
0xbf7e39bc,0x3df0b772,0xbf7ec46d,0xbdc8bd36,0xbe6f0c4d,0x3f78ed3c,0xbee3f40d,0x3f653a48,0xbf226799,0x3f45e403,0xbf4a965e,0x3f1c81b9,
0xbf687c12,0x3ed65a92,0xbf7a9421,0x3e519f65,0xbf7ff35e,0xbca0d6d6,0xbf7853f8,0xbe78cfcc,0xbe9e377a,0x3f737871,0xbf05c277,0x3f5a46a0,
0xbf3504f3,0x3f3504f3,0xbf5a46a0,0x3f05c277,0xbf737871,0x3e9e377a,0xbf7f35f9,0x3da0af2a,0xbf7cd925,0xbe20305b,0xbf6c835e,0xbec3ef15,
0xbec3ef15,0x3f6c835e,0xbf187fc0,0x3f4d9f02,0xbf45e403,0x3f226799,0xbf676bd8,0x3edae880,0xbf7b14be,0x3e47c5c2,0xbf7fb10f,0xbd48fb30,
0xbf74fa0b,0xbe94a031,0xbf5b941a,0xbf039c3d,0xbee87171,0x3f641901,0xbf2a0c73,0x3f3f5cb5,0xbf54db31,0x3f0e39da,0xbf71decf,0x3ea7bf25,
0xbf7f35f9,0x3da0af2a,0xbf7c0361,0xbe3403f1,0xbf687c12,0xbed65a92,0xbf45e403,0xbf226799,0xbf05c277,0x3f5a46a0,0xbf3a4582,0x3f2f9c32,
0xbf61c598,0x3ef15aea,0xbf79805c,0x3e6542e9,0xbf7fcd79,0xbd20cee7,0xbf743c41,0xbe996dba,0xbf579b8c,0xbf0a04f8,0xbf2beb4a,0xbf3daef9,
0xbf167918,0x3f4f1bbd,0xbf490a88,0x3f1e7cf1,0xbf6c835e,0x3ec3ef15,0xbf7e39bc,0x3df0b772,0xbf7cd925,0xbe20305b,0xbf687c12,0xbed65a92,
0xbf42a9f7,0xbf26423a,0xbf0e39da,0xbf54db31,0xbf26423a,0x3f42a9f7,0xbf563e03,0x3f0c2124,0xbf74fa0b,0x3e94a031,0xbf7ffcd7,0x3c20d8d2,
0xbf766377,0xbe8afa3e,0xbf58f3c4,0xbf07e565,0xbf2a0c73,0xbf3f5cb5,0xbedae880,0xbf676bd8,0xbf3504f3,0x3f3504f3,0xbf61c598,0x3ef15aea,
0xbf7b14be,0x3e47c5c2,0xbf7ec46d,0xbdc8bd36,0xbf6c835e,0xbec3ef15,0xbf45e403,0xbf226799,0xbf0e39da,0xbf54db31,0xbe94a031,0xbf74fa0b,
0xbf42a9f7,0x3f26423a,0xbf6b8a3d,0x3ec8917e,0xbf7ec46d,0x3dc8bd36,0xbf7a9421,0xbe519f65,0xbf5f5be6,0xbefa2c90,0xbf2f9c32,0xbf3a4582,
0xbedf7108,0xbf6655e7,0xbe164083,0xbf7d3aac,0x3f800000,0,0x3f800000,0,0x3f800000,0,0x3f800000,0,
0x3f800000,0,0x3f800000,0,0x3f800000,0,0x3f800000,0,0x3f7cd925,0x3e20305b,0x3f7c7160,0x3e2a1c3f,
0x3f7c0361,0x3e3403f1,0x3f7b8f2a,0x3e3de731,0x3f800000,0,0x3f7ffcd7,0x3c20d8d2,0x3f7ff35e,0x3ca0d6d6,0x3f7fe394,0x3cf13d4c,
0x3f737871,0x3e9e377a,0x3f71decf,0x3ea7bf25,0x3f702d4f,0x3eb13641,0x3f6e641a,0x3eba9be1,0x3f800000,0,0x3f7ff35e,0x3ca0d6d6,
0x3f7fcd79,0x3d20cee7,0x3f7f8e56,0x3d712283,0x3f641901,0x3ee87171,0x3f609384,0x3ef5c6c5,0x3f5cdc29,0x3f0172c3,0x3f58f3c4,0x3f07e565,
0x3f800000,0,0x3f7fe394,0x3cf13d4c,0x3f7f8e56,0x3d712283,0x3f7f0059,0x3db4b86a,0x3f4f1bbd,0x3f167918,0x3f490a88,0x3f1e7cf1,
0x3f42a9f7,0x3f26423a,0x3f3bfc8f,0x3f2dc5e3,0x3f800000,0,0x3f7fcd79,0x3d20cee7,0x3f7f35f9,0x3da0af2a,0x3f7e39bc,0x3df0b772,
0x3f3504f3,0x3f3504f3,0x3f2beb4a,0x3f3daef9,0x3f226799,0x3f45e403,0x3f187fc0,0x3f4d9f02,0x3f800000,0,0x3f7fb10f,0x3d48fb30,
0x3f7ec46d,0x3dc8bd36,0x3f7d3aac,0x3e164083,0x3f167918,0x3f4f1bbd,0x3f0a04f8,0x3f579b8c,0x3efa2c90,0x3f5f5be6,0x3edf7108,0x3f6655e7,
0x3f800000,0,0x3f7f8e56,0x3d712283,0x3f7e39bc,0x3df0b772,0x3f7c0361,0x3e3403f1,0x3ee87171,0x3f641901,0x3ec8917e,0x3f6b8a3d,
0x3ea7bf25,0x3f71decf,0x3e862210,0x3f770f11,0x3f800000,0,0x3f7f654e,0x3d8ca1f2,0x3f7d95f4,0x3e0c4cf7,0x3f7a9421,0x3e519f65,
0x3e9e377a,0x3f737871,0x3e6f0c4d,0x3f78ed3c,0x3e20305b,0x3f7cd925,0x3da0af2a,0x3f7f35f9,0x3f800000,0,0x3f7f35f9,0x3da0af2a,
0x3f7cd925,0x3e20305b,0x3f78ed3c,0x3e6f0c4d,0x3e20305b,0x3f7cd925,0x3d8ca1f2,0x3f7f654e,0xbca0d6d6,0x3f7ff35e,0xbddcbd0d,0x3f7e8238,
0x3f800000,0,0x3f7f0059,0x3db4b86a,0x3f7c0361,0x3e3403f1,0x3f770f11,0x3e862210,0x248d3132,0x3f800000,0xbdc8bd36,0x3f7ec46d,
0xbe47c5c2,0x3f7b14be,0xbe94a031,0x3f74fa0b,0x3f800000,0,0x3f7ec46d,0x3dc8bd36,0x3f7b14be,0x3e47c5c2,0x3f74fa0b,0x3e94a031,
0xbe20305b,0x3f7cd925,0xbe862210,0x3f770f11,0xbeba9be1,0x3f6e641a,0xbeece91a,0x3f62f219,0x3f800000,0,0x3f7e8238,0x3ddcbd0d,
0x3f7a0d54,0x3e5b73dc,0x3f72ae9e,0x3ea2fd52,0xbe9e377a,0x3f737871,0xbed65a92,0x3f687c12,0xbf05c277,0x3f5a46a0,0xbf1e7cf1,0x3f490a88,
0x3f800000,0,0x3f7e39bc,0x3df0b772,0x3f78ed3c,0x3e6f0c4d,0x3f702d4f,0x3eb13641,0xbee87171,0x3f641901,0xbf104f0e,0x3f53731f,
0xbf2a0c73,0x3f3f5cb5,0xbf4105b8,0x3f28296a,0x3f800000,0,0x3f7deafa,0x3e0255f4,0x3f77b493,0x3e814693,0x3f6d76aa,0x3ebf47d7,
0xbf167918,0x3f4f1bbd,0xbf316e2c,0x3f3889dc,0xbf490a88,0x3f1e7cf1,0xbf5cdc29,0x3f0172c3,0x3f800000,0,0x3f7d95f4,0x3e0c4cf7,
0x3f766377,0x3e8afa3e,0x3f6a8b4b,0x3ecd2ef3,0xbf3504f3,0x3f3504f3,0xbf4d9f02,0x3f187fc0,0xbf61c598,0x3ef15aea,0xbf710908,0x3eac7cd4,
0x3f800000,0,0x3f7d3aac,0x3e164083,0x3f74fa0b,0x3e94a031,0x3f676bd8,0x3edae880,0xbf4f1bbd,0x3f167918,0xbf641901,0x3ee87171,
0xbf737871,0x3e9e377a,0xbf7cd925,0x3e20305b,0x3f800000,0,0x3f7cd925,0x3e20305b,0x3f737871,0x3e9e377a,0x3f641901,0x3ee87171,
0xbf641901,0x3ee87171,0xbf743c41,0x3e996dba,0xbf7d95f4,0x3e0c4cf7,0xbf7fe394,0xbcf13d4c,0x3f800000,0,0x3f7c7160,0x3e2a1c3f,
0x3f71decf,0x3ea7bf25,0x3f609384,0x3ef5c6c5,0xbf737871,0x3e9e377a,0xbf7d95f4,0x3e0c4cf7,0xbf7fcd79,0xbd20cee7,0xbf7a0d54,0xbe5b73dc,
0x3f800000,0,0x3f7c0361,0x3e3403f1,0x3f702d4f,0x3eb13641,0x3f5cdc29,0x3f0172c3,0xbf7cd925,0x3e20305b,0xbf7fe394,0xbcf13d4c,
0xbf7a0d54,0xbe5b73dc,0xbf6b8a3d,0xbec8917e,0x3f800000,0,0x3f7b8f2a,0x3e3de731,0x3f6e641a,0x3eba9be1,0x3f58f3c4,0x3f07e565,
0xbf800000,0x250d3132,0xbf7b14be,0xbe47c5c2,0xbf6c835e,0xbec3ef15,0xbf54db31,0xbf0e39da,0x3f800000,0,0x3f7b14be,0x3e47c5c2,
0x3f6c835e,0x3ec3ef15,0x3f54db31,0x3f0e39da,0xbf7cd925,0xbe20305b,0xbf6f4ba8,0xbeb5eb4f,0xbf579b8c,0xbf0a04f8,0xbf36c9a9,0xbf333bc6,
0x3f800000,0,0x3f7a9421,0x3e519f65,0x3f6a8b4b,0x3ecd2ef3,0x3f50935b,0x3f146eba,0xbf737871,0xbe9e377a,0xbf5cdc29,0xbf0172c3,
0xbf3bfc8f,0xbf2dc5e3,0xbf1260b2,0xbf5205d4,0x3f800000,0,0x3f7a0d54,0x3e5b73dc,0x3f687c12,0x3ed65a92,0x3f4c1d35,0x3f1a82a4,
0xbf641901,0xbee87171,0xbf444969,0xbf2456f1,0xbf1a82a4,0xbf4c1d35,0xbed1c759,0xbf698690,0x3f800000,0,0x3f79805c,0x3e6542e9,
0x3f6655e7,0x3edf7108,0x3f4779bc,0x3f207440,0xbf4f1bbd,0xbf167918,0xbf26423a,0xbf42a9f7,0xbee87171,0xbf641901,0xbe6f0c4d,0xbf78ed3c,
0x3f800000,0,0x3f78ed3c,0x3e6f0c4d,0x3f641901,0x3ee87171,0x3f42a9f7,0x3f26423a,0xbf3504f3,0xbf3504f3,0xbf039c3d,0xbf5b941a,
0xbe94a031,0xbf74fa0b,0xbd48fb30,0xbf7fb10f,0x3f800000,0,0x3f7853f8,0x3e78cfcc,0x3f61c598,0x3ef15aea,0x3f3daef9,0x3f2beb4a,
0xbf167918,0xbf4f1bbd,0xbeba9be1,0xbf6e641a,0xbdf0b772,0xbf7e39bc,0x3e0c4cf7,0xbf7d95f4,0x3f800000,0,0x3f77b493,0x3e814693,
0x3f5f5be6,0x3efa2c90,0x3f3889dc,0x3f316e2c,0xbee87171,0xbf641901,0xbe519f65,0xbf7a9421,0x3d712283,0xbf7f8e56,0x3ea2fd52,0xbf72ae9e,
0x3f800000,0,0x3f770f11,0x3e862210,0x3f5cdc29,0x3f0172c3,0x3f333bc6,0x3f36c9a9,0xbe9e377a,0xbf737871,0xbd20cee7,0xbf7fcd79,
0x3e6f0c4d,0xbf78ed3c,0x3efa2c90,0xbf5f5be6,0x3f800000,0,0x3f766377,0x3e8afa3e,0x3f5a46a0,0x3f05c277,0x3f2dc5e3,0x3f3bfc8f,
0xbe20305b,0xbf7cd925,0x3e0255f4,0xbf7deafa,0x3ecd2ef3,0xbf6a8b4b,0x3f2456f1,0xbf444969,0x3f800000,0,0x3f75b1c9,0x3e8fcefe,
0x3f579b8c,0x3f0a04f8,0x3f28296a,0x3f4105b8,0xa553c9ca,0xbf800000,0x3e94a031,0xbf74fa0b,0x3f0e39da,0xbf54db31,0x3f45e403,0xbf226799,
0x3f800000,0,0x3f74fa0b,0x3e94a031,0x3f54db31,0x3f0e39da,0x3f226799,0x3f45e403,0x3e20305b,0xbf7cd925,0x3ee3f40d,0xbf653a48,
0x3f316e2c,0xbf3889dc,0x3f609384,0xbef5c6c5,0x3f800000,0,0x3f743c41,0x3e996dba,0x3f5205d4,0x3f1260b2,0x3f1c81b9,0x3f4a965e,
0x3f800000,0,0x3f800000,0,0x3f800000,0,0x3f800000,0,0x3f800000,0,0x3f800000,0,
0x3f800000,0,0x3f800000,0,0x3f7fcd79,0x3d20cee7,0x3f7fb10f,0x3d48fb30,0x3f7f8e56,0x3d712283,0x3f7f654e,0x3d8ca1f2,
0x3f7f35f9,0x3da0af2a,0x3f7f0059,0x3db4b86a,0x3f7ec46d,0x3dc8bd36,0x3f7e8238,0x3ddcbd0d,0x3f7f35f9,0x3da0af2a,0x3f7ec46d,0x3dc8bd36,
0x3f7e39bc,0x3df0b772,0x3f7d95f4,0x3e0c4cf7,0x3f7cd925,0x3e20305b,0x3f7c0361,0x3e3403f1,0x3f7b14be,0x3e47c5c2,0x3f7a0d54,0x3e5b73dc,
0x3f7e39bc,0x3df0b772,0x3f7d3aac,0x3e164083,0x3f7c0361,0x3e3403f1,0x3f7a9421,0x3e519f65,0x3f78ed3c,0x3e6f0c4d,0x3f770f11,0x3e862210,
0x3f74fa0b,0x3e94a031,0x3f72ae9e,0x3ea2fd52,0x3f7cd925,0x3e20305b,0x3f7b14be,0x3e47c5c2,0x3f78ed3c,0x3e6f0c4d,0x3f766377,0x3e8afa3e,
0x3f737871,0x3e9e377a,0x3f702d4f,0x3eb13641,0x3f6c835e,0x3ec3ef15,0x3f687c12,0x3ed65a92,0x3f7b14be,0x3e47c5c2,0x3f7853f8,0x3e78cfcc,
0x3f74fa0b,0x3e94a031,0x3f710908,0x3eac7cd4,0x3f6c835e,0x3ec3ef15,0x3f676bd8,0x3edae880,0x3f61c598,0x3ef15aea,0x3f5b941a,0x3f039c3d,
0x3f78ed3c,0x3e6f0c4d,0x3f74fa0b,0x3e94a031,0x3f702d4f,0x3eb13641,0x3f6a8b4b,0x3ecd2ef3,0x3f641901,0x3ee87171,0x3f5cdc29,0x3f0172c3,
0x3f54db31,0x3f0e39da,0x3f4c1d35,0x3f1a82a4,0x3f766377,0x3e8afa3e,0x3f710908,0x3eac7cd4,0x3f6a8b4b,0x3ecd2ef3,0x3f62f219,0x3eece91a,
0x3f5a46a0,0x3f05c277,0x3f50935b,0x3f146eba,0x3f45e403,0x3f226799,0x3f3a4582,0x3f2f9c32,0x3f737871,0x3e9e377a,0x3f6c835e,0x3ec3ef15,
0x3f641901,0x3ee87171,0x3f5a46a0,0x3f05c277,0x3f4f1bbd,0x3f167918,0x3f42a9f7,0x3f26423a,0x3f3504f3,0x3f3504f3,0x3f26423a,0x3f42a9f7,
0x3f702d4f,0x3eb13641,0x3f676bd8,0x3edae880,0x3f5cdc29,0x3f0172c3,0x3f50935b,0x3f146eba,0x3f42a9f7,0x3f26423a,0x3f333bc6,0x3f36c9a9,
0x3f226799,0x3f45e403,0x3f104f0e,0x3f53731f,0x3f6c835e,0x3ec3ef15,0x3f61c598,0x3ef15aea,0x3f54db31,0x3f0e39da,0x3f45e403,0x3f226799,
0x3f3504f3,0x3f3504f3,0x3f226799,0x3f45e403,0x3f0e39da,0x3f54db31,0x3ef15aea,0x3f61c598,0x3f687c12,0x3ed65a92,0x3f5b941a,0x3f039c3d,
0x3f4c1d35,0x3f1a82a4,0x3f3a4582,0x3f2f9c32,0x3f26423a,0x3f42a9f7,0x3f104f0e,0x3f53731f,0x3ef15aea,0x3f61c598,0x3ebf47d7,0x3f6d76aa,
0x3f641901,0x3ee87171,0x3f54db31,0x3f0e39da,0x3f42a9f7,0x3f26423a,0x3f2dc5e3,0x3f3bfc8f,0x3f167918,0x3f4f1bbd,0x3efa2c90,0x3f5f5be6,
0x3ec3ef15,0x3f6c835e,0x3e8afa3e,0x3f766377,0x3f5f5be6,0x3efa2c90,0x3f4d9f02,0x3f187fc0,0x3f3889dc,0x3f316e2c,0x3f207440,0x3f4779bc,
0x3f05c277,0x3f5a46a0,0x3ed1c759,0x3f698690,0x3e94a031,0x3f74fa0b,0x3e2a1c3f,0x3f7c7160,0x3f5a46a0,0x3f05c277,0x3f45e403,0x3f226799,
0x3f2dc5e3,0x3f3bfc8f,0x3f1260b2,0x3f5205d4,0x3ee87171,0x3f641901,0x3ea7bf25,0x3f71decf,0x3e47c5c2,0x3f7b14be,0x3d712283,0x3f7f8e56,
0x3f54db31,0x3f0e39da,0x3f3daef9,0x3f2beb4a,0x3f226799,0x3f45e403,0x3f039c3d,0x3f5b941a,0x3ec3ef15,0x3f6c835e,0x3e78cfcc,0x3f7853f8,
0x3dc8bd36,0x3f7ec46d,0xbd48fb30,0x3f7fb10f,0x3f4f1bbd,0x3f167918,0x3f3504f3,0x3f3504f3,0x3f167918,0x3f4f1bbd,0x3ee87171,0x3f641901,
0x3e9e377a,0x3f737871,0x3e20305b,0x3f7cd925,0x248d3132,0x3f800000,0xbe20305b,0x3f7cd925,0x3f490a88,0x3f1e7cf1,0x3f2beb4a,0x3f3daef9,
0x3f0a04f8,0x3f579b8c,0x3ec8917e,0x3f6b8a3d,0x3e6f0c4d,0x3f78ed3c,0x3d8ca1f2,0x3f7f654e,0xbdc8bd36,0x3f7ec46d,0xbe862210,0x3f770f11,
0x3f42a9f7,0x3f26423a,0x3f226799,0x3f45e403,0x3efa2c90,0x3f5f5be6,0x3ea7bf25,0x3f71decf,0x3e20305b,0x3f7cd925,0xbca0d6d6,0x3f7ff35e,
0xbe47c5c2,0x3f7b14be,0xbeba9be1,0x3f6e641a,0x3f3bfc8f,0x3f2dc5e3,0x3f187fc0,0x3f4d9f02,0x3edf7108,0x3f6655e7,0x3e862210,0x3f770f11,
0x3da0af2a,0x3f7f35f9,0xbddcbd0d,0x3f7e8238,0xbe94a031,0x3f74fa0b,0xbeece91a,0x3f62f219,0x3f3504f3,0x3f3504f3,0x3f0e39da,0x3f54db31,
0x3ec3ef15,0x3f6c835e,0x3e47c5c2,0x3f7b14be,0x248d3132,0x3f800000,0xbe47c5c2,0x3f7b14be,0xbec3ef15,0x3f6c835e,0xbf0e39da,0x3f54db31,
0x3f2dc5e3,0x3f3bfc8f,0x3f039c3d,0x3f5b941a,0x3ea7bf25,0x3f71decf,0x3e0255f4,0x3f7deafa,0xbda0af2a,0x3f7f35f9,0xbe8fcefe,0x3f75b1c9,
0xbef15aea,0x3f61c598,0xbf2456f1,0x3f444969,0x3f26423a,0x3f42a9f7,0x3ef15aea,0x3f61c598,0x3e8afa3e,0x3f766377,0x3d712283,0x3f7f8e56,
0xbe20305b,0x3f7cd925,0xbeba9be1,0x3f6e641a,0xbf0e39da,0x3f54db31,0xbf3889dc,0x3f316e2c,0x3f1e7cf1,0x3f490a88,0x3edae880,0x3f676bd8,
0x3e5b73dc,0x3f7a0d54,0xbc20d8d2,0x3f7ffcd7,0xbe6f0c4d,0x3f78ed3c,0xbee3f40d,0x3f653a48,0xbf226799,0x3f45e403,0xbf4a965e,0x3f1c81b9,
0x3f167918,0x3f4f1bbd,0x3ec3ef15,0x3f6c835e,0x3e20305b,0x3f7cd925,0xbda0af2a,0x3f7f35f9,0xbe9e377a,0x3f737871,0xbf05c277,0x3f5a46a0,
0xbf3504f3,0x3f3504f3,0xbf5a46a0,0x3f05c277,0x3f0e39da,0x3f54db31,0x3eac7cd4,0x3f710908,0x3dc8bd36,0x3f7ec46d,0xbe164083,0x3f7d3aac,
0xbec3ef15,0x3f6c835e,0xbf187fc0,0x3f4d9f02,0xbf45e403,0x3f226799,0xbf676bd8,0x3edae880,0x3f05c277,0x3f5a46a0,0x3e94a031,0x3f74fa0b,
0x3d20cee7,0x3f7fcd79,0xbe5b73dc,0x3f7a0d54,0xbee87171,0x3f641901,0xbf2a0c73,0x3f3f5cb5,0xbf54db31,0x3f0e39da,0xbf71decf,0x3ea7bf25,
0x3efa2c90,0x3f5f5be6,0x3e78cfcc,0x3f7853f8,0xbca0d6d6,0x3f7ff35e,0xbe8fcefe,0x3f75b1c9,0xbf05c277,0x3f5a46a0,0xbf3a4582,0x3f2f9c32,
0xbf61c598,0x3ef15aea,0xbf79805c,0x3e6542e9,0x3ee87171,0x3f641901,0x3e47c5c2,0x3f7b14be,0xbda0af2a,0x3f7f35f9,0xbeb13641,0x3f702d4f,
0xbf167918,0x3f4f1bbd,0xbf490a88,0x3f1e7cf1,0xbf6c835e,0x3ec3ef15,0xbf7e39bc,0x3df0b772,0x3ed65a92,0x3f687c12,0x3e164083,0x3f7d3aac,
0xbe0c4cf7,0x3f7d95f4,0xbed1c759,0x3f698690,0xbf26423a,0x3f42a9f7,0xbf563e03,0x3f0c2124,0xbf74fa0b,0x3e94a031,0xbf7ffcd7,0x3c20d8d2,
0x3ec3ef15,0x3f6c835e,0x3dc8bd36,0x3f7ec46d,0xbe47c5c2,0x3f7b14be,0xbef15aea,0x3f61c598,0xbf3504f3,0x3f3504f3,0xbf61c598,0x3ef15aea,
0xbf7b14be,0x3e47c5c2,0xbf7ec46d,0xbdc8bd36,0x3eb13641,0x3f702d4f,0x3d48fb30,0x3f7fb10f,0xbe814693,0x3f77b493,0xbf07e565,0x3f58f3c4,
0xbf42a9f7,0x3f26423a,0xbf6b8a3d,0x3ec8917e,0xbf7ec46d,0x3dc8bd36,0xbf7a9421,0xbe519f65,0x3f800000,0,0x3f800000,0,
0x3f800000,0,0x3f800000,0,0x3f800000,0,0x3f800000,0,0x3f800000,0,0x3f800000,0,
0x3f7e39bc,0x3df0b772,0x3f7deafa,0x3e0255f4,0x3f7d95f4,0x3e0c4cf7,0x3f7d3aac,0x3e164083,0x3f7cd925,0x3e20305b,0x3f7c7160,0x3e2a1c3f,
0x3f7c0361,0x3e3403f1,0x3f7b8f2a,0x3e3de731,0x3f78ed3c,0x3e6f0c4d,0x3f77b493,0x3e814693,0x3f766377,0x3e8afa3e,0x3f74fa0b,0x3e94a031,
0x3f737871,0x3e9e377a,0x3f71decf,0x3ea7bf25,0x3f702d4f,0x3eb13641,0x3f6e641a,0x3eba9be1,0x3f702d4f,0x3eb13641,0x3f6d76aa,0x3ebf47d7,
0x3f6a8b4b,0x3ecd2ef3,0x3f676bd8,0x3edae880,0x3f641901,0x3ee87171,0x3f609384,0x3ef5c6c5,0x3f5cdc29,0x3f0172c3,0x3f58f3c4,0x3f07e565,
0x3f641901,0x3ee87171,0x3f5f5be6,0x3efa2c90,0x3f5a46a0,0x3f05c277,0x3f54db31,0x3f0e39da,0x3f4f1bbd,0x3f167918,0x3f490a88,0x3f1e7cf1,
0x3f42a9f7,0x3f26423a,0x3f3bfc8f,0x3f2dc5e3,0x3f54db31,0x3f0e39da,0x3f4d9f02,0x3f187fc0,0x3f45e403,0x3f226799,0x3f3daef9,0x3f2beb4a,
0x3f3504f3,0x3f3504f3,0x3f2beb4a,0x3f3daef9,0x3f226799,0x3f45e403,0x3f187fc0,0x3f4d9f02,0x3f42a9f7,0x3f26423a,0x3f3889dc,0x3f316e2c,
0x3f2dc5e3,0x3f3bfc8f,0x3f226799,0x3f45e403,0x3f167918,0x3f4f1bbd,0x3f0a04f8,0x3f579b8c,0x3efa2c90,0x3f5f5be6,0x3edf7108,0x3f6655e7,
0x3f2dc5e3,0x3f3bfc8f,0x3f207440,0x3f4779bc,0x3f1260b2,0x3f5205d4,0x3f039c3d,0x3f5b941a,0x3ee87171,0x3f641901,0x3ec8917e,0x3f6b8a3d,
0x3ea7bf25,0x3f71decf,0x3e862210,0x3f770f11,0x3f167918,0x3f4f1bbd,0x3f05c277,0x3f5a46a0,0x3ee87171,0x3f641901,0x3ec3ef15,0x3f6c835e,
0x3e9e377a,0x3f737871,0x3e6f0c4d,0x3f78ed3c,0x3e20305b,0x3f7cd925,0x3da0af2a,0x3f7f35f9,0x3efa2c90,0x3f5f5be6,0x3ed1c759,0x3f698690,
0x3ea7bf25,0x3f71decf,0x3e78cfcc,0x3f7853f8,0x3e20305b,0x3f7cd925,0x3d8ca1f2,0x3f7f654e,0xbca0d6d6,0x3f7ff35e,0xbddcbd0d,0x3f7e8238,
0x3ec3ef15,0x3f6c835e,0x3e94a031,0x3f74fa0b,0x3e47c5c2,0x3f7b14be,0x3dc8bd36,0x3f7ec46d,0x248d3132,0x3f800000,0xbdc8bd36,0x3f7ec46d,
0xbe47c5c2,0x3f7b14be,0xbe94a031,0x3f74fa0b,0x3e8afa3e,0x3f766377,0x3e2a1c3f,0x3f7c7160,0x3d712283,0x3f7f8e56,0xbd48fb30,0x3f7fb10f,
0xbe20305b,0x3f7cd925,0xbe862210,0x3f770f11,0xbeba9be1,0x3f6e641a,0xbeece91a,0x3f62f219,0x3e20305b,0x3f7cd925,0x3d20cee7,0x3f7fcd79,
0xbda0af2a,0x3f7f35f9,0xbe47c5c2,0x3f7b14be,0xbe9e377a,0x3f737871,0xbed65a92,0x3f687c12,0xbf05c277,0x3f5a46a0,0xbf1e7cf1,0x3f490a88,
0x3d20cee7,0x3f7fcd79,0xbdb4b86a,0x3f7f0059,0xbe5b73dc,0x3f7a0d54,0xbeac7cd4,0x3f710908,0xbee87171,0x3f641901,0xbf104f0e,0x3f53731f,
0xbf2a0c73,0x3f3f5cb5,0xbf4105b8,0x3f28296a,0xbda0af2a,0x3f7f35f9,0xbe5b73dc,0x3f7a0d54,0xbeb13641,0x3f702d4f,0xbef15aea,0x3f61c598,
0xbf167918,0x3f4f1bbd,0xbf316e2c,0x3f3889dc,0xbf490a88,0x3f1e7cf1,0xbf5cdc29,0x3f0172c3,0xbe47c5c2,0x3f7b14be,0xbeac7cd4,0x3f710908,
0xbef15aea,0x3f61c598,0xbf187fc0,0x3f4d9f02,0xbf3504f3,0x3f3504f3,0xbf4d9f02,0x3f187fc0,0xbf61c598,0x3ef15aea,0xbf710908,0x3eac7cd4,
0xbe9e377a,0x3f737871,0xbee87171,0x3f641901,0xbf167918,0x3f4f1bbd,0xbf3504f3,0x3f3504f3,0xbf4f1bbd,0x3f167918,0xbf641901,0x3ee87171,
0xbf737871,0x3e9e377a,0xbf7cd925,0x3e20305b,0xbed65a92,0x3f687c12,0xbf104f0e,0x3f53731f,0xbf316e2c,0x3f3889dc,0xbf4d9f02,0x3f187fc0,
0xbf641901,0x3ee87171,0xbf743c41,0x3e996dba,0xbf7d95f4,0x3e0c4cf7,0xbf7fe394,0xbcf13d4c,0xbf05c277,0x3f5a46a0,0xbf2a0c73,0x3f3f5cb5,
0xbf490a88,0x3f1e7cf1,0xbf61c598,0x3ef15aea,0xbf737871,0x3e9e377a,0xbf7d95f4,0x3e0c4cf7,0xbf7fcd79,0xbd20cee7,0xbf7a0d54,0xbe5b73dc,
0xbf1e7cf1,0x3f490a88,0xbf4105b8,0x3f28296a,0xbf5cdc29,0x3f0172c3,0xbf710908,0x3eac7cd4,0xbf7cd925,0x3e20305b,0xbf7fe394,0xbcf13d4c,
0xbf7a0d54,0xbe5b73dc,0xbf6b8a3d,0xbec8917e,0xbf3504f3,0x3f3504f3,0xbf54db31,0x3f0e39da,0xbf6c835e,0x3ec3ef15,0xbf7b14be,0x3e47c5c2,
0xbf800000,0x250d3132,0xbf7b14be,0xbe47c5c2,0xbf6c835e,0xbec3ef15,0xbf54db31,0xbf0e39da,0xbf490a88,0x3f1e7cf1,0xbf653a48,0x3ee3f40d,
0xbf77b493,0x3e814693,0xbf7fb10f,0x3d48fb30,0xbf7cd925,0xbe20305b,0xbf6f4ba8,0xbeb5eb4f,0xbf579b8c,0xbf0a04f8,0xbf36c9a9,0xbf333bc6,
0xbf5a46a0,0x3f05c277,0xbf71decf,0x3ea7bf25,0xbf7e39bc,0x3df0b772,0xbf7ec46d,0xbdc8bd36,0xbf737871,0xbe9e377a,0xbf5cdc29,0xbf0172c3,
0xbf3bfc8f,0xbf2dc5e3,0xbf1260b2,0xbf5205d4,0xbf687c12,0x3ed65a92,0xbf7a9421,0x3e519f65,0xbf7ff35e,0xbca0d6d6,0xbf7853f8,0xbe78cfcc,
0xbf641901,0xbee87171,0xbf444969,0xbf2456f1,0xbf1a82a4,0xbf4c1d35,0xbed1c759,0xbf698690,0xbf737871,0x3e9e377a,0xbf7f35f9,0x3da0af2a,
0xbf7cd925,0xbe20305b,0xbf6c835e,0xbec3ef15,0xbf4f1bbd,0xbf167918,0xbf26423a,0xbf42a9f7,0xbee87171,0xbf641901,0xbe6f0c4d,0xbf78ed3c,
0xbf7b14be,0x3e47c5c2,0xbf7fb10f,0xbd48fb30,0xbf74fa0b,0xbe94a031,0xbf5b941a,0xbf039c3d,0xbf3504f3,0xbf3504f3,0xbf039c3d,0xbf5b941a,
0xbe94a031,0xbf74fa0b,0xbd48fb30,0xbf7fb10f,0xbf7f35f9,0x3da0af2a,0xbf7c0361,0xbe3403f1,0xbf687c12,0xbed65a92,0xbf45e403,0xbf226799,
0xbf167918,0xbf4f1bbd,0xbeba9be1,0xbf6e641a,0xbdf0b772,0xbf7e39bc,0x3e0c4cf7,0xbf7d95f4,0xbf7fcd79,0xbd20cee7,0xbf743c41,0xbe996dba,
0xbf579b8c,0xbf0a04f8,0xbf2beb4a,0xbf3daef9,0xbee87171,0xbf641901,0xbe519f65,0xbf7a9421,0x3d712283,0xbf7f8e56,0x3ea2fd52,0xbf72ae9e,
0xbf7cd925,0xbe20305b,0xbf687c12,0xbed65a92,0xbf42a9f7,0xbf26423a,0xbf0e39da,0xbf54db31,0xbe9e377a,0xbf737871,0xbd20cee7,0xbf7fcd79,
0x3e6f0c4d,0xbf78ed3c,0x3efa2c90,0xbf5f5be6,0xbf766377,0xbe8afa3e,0xbf58f3c4,0xbf07e565,0xbf2a0c73,0xbf3f5cb5,0xbedae880,0xbf676bd8,
0xbe20305b,0xbf7cd925,0x3e0255f4,0xbf7deafa,0x3ecd2ef3,0xbf6a8b4b,0x3f2456f1,0xbf444969,0xbf6c835e,0xbec3ef15,0xbf45e403,0xbf226799,
0xbf0e39da,0xbf54db31,0xbe94a031,0xbf74fa0b,0xa553c9ca,0xbf800000,0x3e94a031,0xbf74fa0b,0x3f0e39da,0xbf54db31,0x3f45e403,0xbf226799,
0xbf5f5be6,0xbefa2c90,0xbf2f9c32,0xbf3a4582,0xbedf7108,0xbf6655e7,0xbe164083,0xbf7d3aac,0x3e20305b,0xbf7cd925,0x3ee3f40d,0xbf653a48,
0x3f316e2c,0xbf3889dc,0x3f609384,0xbef5c6c5,
};
__device__ __align__(128) const uint32_t T_C20[880] = {
0,0,0,0,0,0,0,0,0,0,0,0,
0,0,0,0,0,0,0,0,0,0,0,0,
0,0,0,0,0,0,0,0,0,0,0,0,
0,0,0,0,0,0,0,0,0,0,0,0,
0x3f80,0x3f80,0x3f80,0x3f80,0x3f80,0x3e9e3f73,0x3f163f4f,0x3f4f3f16,0x3f80,0x3f163f4f,0x3f733e9e,0x3f73be9e,
0x3f80,0x3f4f3f16,0x3f73be9e,0x3e9ebf73,0x3f80,0x3f733e9e,0x3f16bf4f,0xbf16bf4f,0x3f80,0x3f80248d,0x250dbf80,0xbf80a554,
0x3f80,0x3f73be9e,0xbf16bf4f,0xbf163f4f,0x3f80,0x3f4fbf16,0xbf73be9e,0x3e9e3f73,0x3f80,0x3f16bf4f,0xbf733e9e,0x3f733e9e,
0x3f80,0x3e9ebf73,0xbf163f4f,0x3f4fbf16,0x3f80,0x250dbf80,0x3f80,0x250dbf80,0x3f80,0xbe9ebf73,0x3f163f4f,0xbf4fbf16,
0x3f80,0xbf16bf4f,0x3f733e9e,0xbf733e9e,0x3f80,0xbf4fbf16,0x3f73be9e,0xbe9e3f73,0x3f80,0xbf73be9e,0x3f16bf4f,0x3f163f4f,
0x3f80,0xbf80a554,0x250dbf80,0x3f80248d,0x3f80,0xbf733e9e,0xbf16bf4f,0x3f16bf4f,0x3f80,0xbf4f3f16,0xbf73be9e,0xbe9ebf73,
0x3f80,0xbf163f4f,0xbf733e9e,0xbf73be9e,0x3f80,0xbe9e3f73,0xbf163f4f,0xbf4f3f16,0,0,0,0,
0,0,0,0,0,0,0,0,0,0,0,0,
0,0,0,0,0,0,0,0,0,0,0,0,
0,0,0,0,0,0,0,0,0,0,0,0,
0,0,0,0,0,0,0,0,0,0,0,0,
0,0,0,0,0,0,0,0,0,0,0,0,
0,0,0,0,0,0,0,0,0,0,0,0,
0,0,0,0,0,0,0,0,0,0,0,0,
0,0,0,0,0,0,0,0,0x3f80,0x3f80,0x3f80,0x3f80,
0x3f733e9e,0x3f80248d,0x3f73be9e,0x3f4fbf16,0x3f16bf4f,0x250dbf80,0xbf16bf4f,0xbf73be9e,0xbf16bf4f,0xbf80a554,0xbf163f4f,0x3e9e3f73,
0xbf733e9e,0x3f80,0x3f733e9e,0x3f16bf4f,0x3f80,0x3f80248d,0x250dbf80,0xbf80a554,0x3f733e9e,0x250dbf80,0xbf733e9e,0x3f163f4f,
0x3f16bf4f,0xbf80a554,0x3f163f4f,0x3e9ebf73,0xbf16bf4f,0x3f80,0x3f16bf4f,0xbf733e9e,0xbf733e9e,0x3f80248d,0xbf73be9e,0x3f4f3f16,
0x3f80,0x250dbf80,0x3f80,0x250dbf80,0x3f733e9e,0xbf80a554,0x3f73be9e,0xbf4f3f16,0x3f16bf4f,0x3f80,0xbf16bf4f,0x3f733e9e,
0xbf16bf4f,0x3f80248d,0xbf163f4f,0xbe9ebf73,0xbf733e9e,0x250dbf80,0x3f733e9e,0xbf163f4f,0x3f80,0xbf80a554,0x250dbf80,0x3f80248d,
0x3f733e9e,0x3f80,0xbf733e9e,0xbf16bf4f,0x3f16bf4f,0x3f80248d,0x3f163f4f,0xbe9e3f73,0xbf16bf4f,0x250dbf80,0x3f16bf4f,0x3f73be9e,
0xbf733e9e,0xbf80a554,0xbf73be9e,0xbf4fbf16,0,0,0,0,0,0,0,0,
0,0,0,0,0,0,0,0,0,0,0,0,
0,0,0,0,0,0,0,0,0,0,0,0,
0,0,0,0,0,0,0,0,0,0,0,0,
0,0,0,0,0,0,0,0,0,0,0,0,
0,0,0,0,0,0,0,0,0,0,0,0,
0,0,0,0,0,0,0,0,0,0,0,0,
0,0,0,0,0,0,0,0,0,0,0,0,
0,0,0,0,0x3f80,0x3f80,0x3f80,0x3f80,0x3f16bf4f,0x3e9ebf73,0x250dbf80,0xbe9ebf73,
0xbf733e9e,0xbf163f4f,0x3f80,0x3f163f4f,0x3f733e9e,0x3f4fbf16,0x250dbf80,0xbf4fbf16,0xbf16bf4f,0xbf733e9e,0x3f80,0x3f733e9e,
0x3f80,0x3f80248d,0x250dbf80,0xbf80a554,0x3f16bf4f,0xbf73be9e,0x3f80,0x3f73be9e,0xbf733e9e,0x3f4f3f16,0x250dbf80,0xbf4f3f16,
0x3f733e9e,0xbf16bf4f,0x3f80,0x3f16bf4f,0xbf16bf4f,0x3e9e3f73,0x250dbf80,0xbe9e3f73,0x3f80,0x250dbf80,0x3f80,0x250dbf80,
0x3f16bf4f,0xbe9e3f73,0x250dbf80,0x3e9e3f73,0xbf733e9e,0x3f16bf4f,0x3f80,0xbf16bf4f,0x3f733e9e,0xbf4f3f16,0x250dbf80,0x3f4f3f16,
0xbf16bf4f,0x3f73be9e,0x3f80,0xbf73be9e,0x3f80,0xbf80a554,0x250dbf80,0x3f80248d,0x3f16bf4f,0x3f733e9e,0x3f80,0xbf733e9e,
0xbf733e9e,0xbf4fbf16,0x250dbf80,0x3f4fbf16,0x3f733e9e,0x3f163f4f,0x3f80,0xbf163f4f,0xbf16bf4f,0xbe9ebf73,0x250dbf80,0x3e9ebf73,
0,0,0,0,0,0,0,0,0,0,0,0,
0,0,0,0,0,0,0,0,0,0,0,0,
0,0,0,0,0,0,0,0,0,0,0,0,
0,0,0,0,0,0,0,0,0,0,0,0,
0,0,0,0,0,0,0,0,0,0,0,0,
0,0,0,0,0,0,0,0,0,0,0,0,
0,0,0,0,0,0,0,0,0,0,0,0,
0,0,0,0,0,0,0,0,0,0,0,0,
0x3f80,0x3f80,0x3f80,0x3f80,0xbf16bf4f,0xbf4fbf16,0xbf73be9e,0xbf80a554,0x3f733e9e,0x3f73be9e,0x3f16bf4f,0x250dbf80,
0xbf733e9e,0xbe9e3f73,0x3f163f4f,0x3f80248d,0x3f16bf4f,0xbf16bf4f,0xbf733e9e,0x3f80,0x3f80,0x3f80248d,0x250dbf80,0xbf80a554,
0xbf16bf4f,0xbf163f4f,0x3f733e9e,0x250dbf80,0x3f733e9e,0xbe9ebf73,0xbf163f4f,0x3f80248d,0xbf733e9e,0x3f733e9e,0xbf16bf4f,0x3f80,
0x3f16bf4f,0xbf4f3f16,0x3f73be9e,0xbf80a554,0x3f80,0x250dbf80,0x3f80,0x250dbf80,0xbf16bf4f,0x3f4f3f16,0xbf73be9e,0x3f80248d,
0x3f733e9e,0xbf733e9e,0x3f16bf4f,0x3f80,0xbf733e9e,0x3e9ebf73,0x3f163f4f,0xbf80a554,0x3f16bf4f,0x3f163f4f,0xbf733e9e,0x250dbf80,
0x3f80,0xbf80a554,0x250dbf80,0x3f80248d,0xbf16bf4f,0x3f16bf4f,0x3f733e9e,0x3f80,0x3f733e9e,0x3e9e3f73,0xbf163f4f,0xbf80a554,
0xbf733e9e,0xbf73be9e,0xbf16bf4f,0x250dbf80,0x3f16bf4f,0x3f4fbf16,0x3f73be9e,0x3f80248d,0,0,0,0,
0,0,0,0,0,0,0,0,0,0,0,0,
0,0,0,0,0,0,0,0,0,0,0,0,
0,0,0,0,0,0,0,0,0,0,0,0,
0,0,0,0,0,0,0,0,0,0,0,0,
0,0,0,0,0,0,0,0,0,0,0,0,
0,0,0,0,0,0,0,0,0,0,0,0,
0,0,0,0,0,0,0,0,0,0,0,0,
0,0,0,0,0,0,0,0,0x3f80,0x3f80,0x3f80,0x3f80,
0xbf733e9e,0xbf4f3f16,0xbf163f4f,0xbe9e3f73,0xbf16bf4f,0xbf73be9e,0xbf733e9e,0xbf163f4f,0x3f16bf4f,0xbe9ebf73,0xbf73be9e,0xbf4f3f16,
0x3f733e9e,0x3f16bf4f,0xbf16bf4f,0xbf733e9e,0x3f80,0x3f80248d,0x250dbf80,0xbf80a554,0xbf733e9e,0x3f163f4f,0x3f16bf4f,0xbf73be9e,
0xbf16bf4f,0xbe9e3f73,0x3f73be9e,0xbf4fbf16,0x3f16bf4f,0xbf733e9e,0x3f733e9e,0xbf16bf4f,0x3f733e9e,0xbf4fbf16,0x3f163f4f,0xbe9ebf73,
0x3f80,0x250dbf80,0x3f80,0x250dbf80,0xbf733e9e,0x3f4fbf16,0xbf163f4f,0x3e9ebf73,0xbf16bf4f,0x3f733e9e,0xbf733e9e,0x3f16bf4f,
0x3f16bf4f,0x3e9e3f73,0xbf73be9e,0x3f4fbf16,0x3f733e9e,0xbf163f4f,0xbf16bf4f,0x3f73be9e,0x3f80,0xbf80a554,0x250dbf80,0x3f80248d,
0xbf733e9e,0xbf16bf4f,0x3f16bf4f,0x3f733e9e,0xbf16bf4f,0x3e9ebf73,0x3f73be9e,0x3f4f3f16,0x3f16bf4f,0x3f73be9e,0x3f733e9e,0x3f163f4f,
0x3f733e9e,0x3f4f3f16,0x3f163f4f,0x3e9e3f73,0,0,0,0,0,0,0,0,
0,0,0,0,0,0,0,0,0,0,0,0,
0,0,0,0,0,0,0,0,0,0,0,0,
0,0,0,0,0,0,0,0,0,0,0,0,
0,0,0,0,
};
__device__ __align__(128) const uint32_t T_TW2048[4096] = {
0x3f800000,0,0x3f800000,0,0x3f800000,0,0x3f800000,0,0x3f800000,0,0x3f800000,0,
0x3f800000,0,0x3f800000,0,0x3f800000,0,0x3f7fffb1,0x3b490fc6,0x3f7ffb11,0x3c490e90,0x3f7ff84a,0x3c7b514b,
0x3f7fec43,0x3cc90ab0,0x3f7fe705,0x3ce22a7a,0x3f7fd397,0x3d16c32c,0x3f7fcbe2,0x3d2351cb,0x3f800000,0,0x3f7ffec4,0x3bc90f88,
0x3f7fec43,0x3cc90ab0,0x3f7fe129,0x3cfb49ba,0x3f7fb10f,0x3d48fb30,0x3f7f9c18,0x3d621469,0x3f7f4e6d,0x3d96a905,0x3f7f2f9d,0x3da3308c,
0x3f800000,0,0x3f7ffd39,0x3c16cb58,0x3f7fd397,0x3d16c32c,0x3f7fba9e,0x3d3c6dd5,0x3f7f4e6d,0x3d96a905,0x3f7f1f49,0x3da973ba,
0x3f7e70b0,0x3de1bc2e,0x3f7e2b72,0x3df475c0,0x3f800000,0,0x3f7ffb11,0x3c490e90,0x3f7fb10f,0x3d48fb30,0x3f7f84ab,0x3d7b2b74,
0x3f7ec46d,0x3dc8bd36,0x3f7e70b0,0x3de1bc2e,0x3f7d3aac,0x3e164083,0x3f7cbfc9,0x3e22abb6,0x3f800000,0,0x3f7ff84a,0x3c7b514b,
0x3f7f84ab,0x3d7b2b74,0x3f7f3f54,0x3d9cecf9,0x3f7e1324,0x3dfab273,0x3f7d906e,0x3e0cec4a,0x3f7baccd,0x3e3b6ecf,0x3f7aed37,0x3e4ada4f,
0x3f800000,0,0x3f7ff4e6,0x3c96c9b6,0x3f7f4e6d,0x3d96a905,0x3f7eea9d,0x3dbc3ac3,0x3f7d3aac,0x3e164083,0x3f7c7eb0,0x3e28defc,
0x3f79c79d,0x3e605c13,0x3f78b47b,0x3e72b651,0x3f800000,0,0x3f7ff0e3,0x3cafea69,0x3f7f0e58,0x3dafb680,0x3f7e868b,0x3ddb7d37,
0x3f7c3b28,0x3e2f10a2,0x3f7b3bab,0x3e44b0b9,0x3f778bc5,0x3e827dc0,0x3f76167a,0x3e8d17c0,0x3f800000,0,0x3f7fec43,0x3cc90ab0,
0x3f7ec46d,0x3dc8bd36,0x3f7e1324,0x3dfab273,0x3f7b14be,0x3e47c5c2,0x3f79c79d,0x3e605c13,0x3f74fa0b,0x3e94a031,0x3f731447,0x3ea09ae5,
0x3f800000,0,0x3f7fe705,0x3ce22a7a,0x3f7e70b0,0x3de1bc2e,0x3f7d906e,0x3e0cec4a,0x3f79c79d,0x3e605c13,0x3f7822d1,0x3e7bdba4,
0x3f721352,0x3ea68f12,0x3f6faf1b,0x3eb3dca5,0x3f800000,0,0x3f7fe129,0x3cfb49ba,0x3f7e1324,0x3dfab273,0x3f7cfe73,0x3e1c76de,
0x3f7853f8,0x3e78cfcc,0x3f764d97,0x3e8b9507,0x3f6ed89e,0x3eb8442a,0x3f6be858,0x3ec6d529,0x3f800000,0,0x3f7fdaaf,0x3d0a342f,
0x3f7dabcc,0x3e09cf86,0x3f7c5d3a,0x3e2bf804,0x3f76ba07,0x3e888e93,0x3f74484b,0x3e9920fe,0x3f6b4b0c,0x3ec9b953,0x3f67c187,0x3ed97cb9,
0x3f800000,0,0x3f7fd397,0x3d16c32c,0x3f7d3aac,0x3e164083,0x3f7baccd,0x3e3b6ecf,0x3f74fa0b,0x3e94a031,0x3f721352,0x3ea68f12,
0x3f676bd8,0x3edae880,0x3f633c5a,0x3eebcbbb,0x3f800000,0,0x3f7fcbe2,0x3d2351cb,0x3f7cbfc9,0x3e22abb6,0x3f7aed37,0x3e4ada4f,
0x3f731447,0x3ea09ae5,0x3f6faf1b,0x3eb3dca5,0x3f633c5a,0x3eebcbbb,0x3f5e5aa6,0x3efdbabb,0x3f800000,0,0x3f7fc38f,0x3d2fe007,
0x3f7c3b28,0x3e2f10a2,0x3f7a1e84,0x3e5a3997,0x3f710908,0x3eac7cd4,0x3f6d1c1d,0x3ec1071e,0x3f5ebe05,0x3efc5d27,0x3f591e6a,0x3f07a136,
0x3f800000,0,0x3f7fba9e,0x3d3c6dd5,0x3f7baccd,0x3e3b6ecf,0x3f7940c0,0x3e698bba,0x3f6ed89e,0x3eb8442a,0x3f6a5ad9,0x3ece0bea,
0x3f59f26a,0x3f064b82,0x3f5389c7,0x3f102dd5,0x3f800000,0,0x3f7fb10f,0x3d48fb30,0x3f7b14be,0x3e47c5c2,0x3f7853f8,0x3e78cfcc,
0x3f6c835e,0x3ec3ef15,0x3f676bd8,0x3edae880,0x3f54db31,0x3f0e39da,0x3f4d9f02,0x3f187fc0,0x3f800000,0,0x3f7fa6e3,0x3d55880e,
0x3f7a7302,0x3e541501,0x3f77583a,0x3e840270,0x3f6a09a7,0x3ecf7bca,0x3f644fac,0x3ee79a5d,0x3f4f7a1f,0x3f15f6d9,0x3f476085,0x3f209393,
0x3f800000,0,0x3f7f9c18,0x3d621469,0x3f79c79d,0x3e605c13,0x3f764d97,0x3e8b9507,0x3f676bd8,0x3edae880,0x3f6106f2,0x3ef41f07,
0x3f49d112,0x3f1d7fd1,0x3f40d0da,0x3f286605,0x3f800000,0,0x3f7f90b1,0x3d6ea038,0x3f791298,0x3e6c9a7f,0x3f75341d,0x3e931f35,
0x3f64aa59,0x3ee63375,0x3f5d924d,0x3f003a06,0x3f43e200,0x3f24d225,0x3f39f2ac,0x3f2ff3e6,0x3f800000,0,0x3f7f84ab,0x3d7b2b74,
0x3f7853f8,0x3e78cfcc,0x3f740bdd,0x3e9aa086,0x3f61c598,0x3ef15aea,0x3f59f26a,0x3f064b82,0x3f3daef9,0x3f2beb4a,0x3f32c8c9,0x3f373a23,
0x3f800000,0,0x3f7f7808,0x3d83db0a,0x3f778bc5,0x3e827dc0,0x3f72d4eb,0x3ea21887,0x3f5ebe05,0x3efc5d27,0x3f5627fe,0x3f0c42c9,
0x3f373a23,0x3f32c8c9,0x3f2b561b,0x3f3e35c5,0x3f800000,0,0x3f7f6ac7,0x3d8a200a,0x3f76ba07,0x3e888e93,0x3f718f57,0x3ea986c4,
0x3f5b941a,0x3f039c3d,0x3f5233c6,0x3f121eb0,0x3f3085bb,0x3f396842,0x3f239da9,0x3f44e3f5,0x3f800000,0,0x3f7f5ce9,0x3d9064b4,
0x3f75dec6,0x3e8e9a22,0x3f703b37,0x3eb0eacb,0x3f584853,0x3f08f59b,0x3f4e1689,0x3f17de12,0x3f299415,0x3f3fc767,0x3f1ba299,0x3f4b41fa,
0x3f800000,0,0x3f7f4e6d,0x3d96a905,0x3f74fa0b,0x3e94a031,0x3f6ed89e,0x3eb8442a,0x3f54db31,0x3f0e39da,0x3f49d112,0x3f1d7fd1,
0x3f226799,0x3f45e403,0x3f13682a,0x3f514d3d,0x3f800000,0,0x3f7f3f54,0x3d9cecf9,0x3f740bdd,0x3e9aa086,0x3f6d67a1,0x3ebf926f,
0x3f514d3d,0x3f13682a,0x3f456439,0x3f2302d3,0x3f1b02c6,0x3f4bbbf8,0x3f0af1b7,0x3f570348,0x3f800000,0,0x3f7f2f9d,0x3da3308c,
0x3f731447,0x3ea09ae5,0x3f6be858,0x3ec6d529,0x3f4d9f02,0x3f187fc0,0x3f40d0da,0x3f286605,0x3f13682a,0x3f514d3d,0x3f0242b1,0x3f5c61c7,
0x3f800000,0,0x3f7f1f49,0x3da973ba,0x3f721352,0x3ea68f12,0x3f6a5ad9,0x3ece0bea,0x3f49d112,0x3f1d7fd1,0x3f3c17d9,0x3f2da859,
0x3f0b9a6b,0x3f5695e5,0x3ef2bd43,0x3f61668a,0x3f800000,0,0x3f7f0e58,0x3dafb680,0x3f710908,0x3eac7cd4,0x3f68bf3c,0x3ed53641,
0x3f45e403,0x3f226799,0x3f373a23,0x3f32c8c9,0x3f039c3d,0x3f5b941a,0x3ee0924f,0x3f660f88,0x3f800000,0,0x3f7efcc9,0x3db5f8da,
0x3f6ff573,0x3eb263ef,0x3f671599,0x3edc53c1,0x3f41d870,0x3f273656,0x3f3238aa,0x3f37c655,0x3ef6e0cb,0x3f604621,0x3ece0bea,0x3f6a5ad9,
0x3f800000,0,0x3f7eea9d,0x3dbc3ac3,0x3f6ed89e,0x3eb8442a,0x3f655e0b,0x3ee363fa,0x3f3daef9,0x3f2beb4a,0x3f2d1469,0x3f3ca003,
0x3ee63375,0x3f64aa59,0x3ebb31a0,0x3f6e46be,0x3f800000,0,0x3f7ed7d4,0x3dc27c39,0x3f6db293,0x3ebe1d4a,0x3f6398ac,0x3eea6681,
0x3f396842,0x3f3085bb,0x3f27ce61,0x3f4154e1,0x3ed53641,0x3f68bf3c,0x3ea80b1f,0x3f71d19f,0x3f800000,0,0x3f800000,0,
0x3f800000,0,0x3f800000,0,0x3f800000,0,0x3f800000,0,0x3f800000,0,0x3f800000,0,
0x3f7ffec4,0x3bc90f88,0x3f7ffd39,0x3c16cb58,0x3f7ff4e6,0x3c96c9b6,0x3f7ff0e3,0x3cafea69,0x3f7fe129,0x3cfb49ba,0x3f7fdaaf,0x3d0a342f,
0x3f7fc38f,0x3d2fe007,0x3f7fba9e,0x3d3c6dd5,0x3f7ffb11,0x3c490e90,0x3f7ff4e6,0x3c96c9b6,0x3f7fd397,0x3d16c32c,0x3f7fc38f,0x3d2fe007,
0x3f7f84ab,0x3d7b2b74,0x3f7f6ac7,0x3d8a200a,0x3f7f0e58,0x3dafb680,0x3f7eea9d,0x3dbc3ac3,0x3f7ff4e6,0x3c96c9b6,0x3f7fe705,0x3ce22a7a,
0x3f7f9c18,0x3d621469,0x3f7f7808,0x3d83db0a,0x3f7eea9d,0x3dbc3ac3,0x3f7eb069,0x3dcefdb7,0x3f7de0b1,0x3e039502,0x3f7d906e,0x3e0cec4a,
0x3f7fec43,0x3cc90ab0,0x3f7fd397,0x3d16c32c,0x3f7f4e6d,0x3d96a905,0x3f7f0e58,0x3dafb680,0x3f7e1324,0x3dfab273,0x3f7dabcc,0x3e09cf86,
0x3f7c3b28,0x3e2f10a2,0x3f7baccd,0x3e3b6ecf,0x3f7fe129,0x3cfb49ba,0x3f7fba9e,0x3d3c6dd5,0x3f7eea9d,0x3dbc3ac3,0x3f7e868b,0x3ddb7d37,
0x3f7cfe73,0x3e1c76de,0x3f7c5d3a,0x3e2bf804,0x3f7a1e84,0x3e5a3997,0x3f7940c0,0x3e698bba,0x3f7fd397,0x3d16c32c,0x3f7f9c18,0x3d621469,
0x3f7e70b0,0x3de1bc2e,0x3f7de0b1,0x3e039502,0x3f7baccd,0x3e3b6ecf,0x3f7ac516,0x3e4dee60,0x3f778bc5,0x3e827dc0,0x3f764d97,0x3e8b9507,
0x3f7fc38f,0x3d2fe007,0x3f7f7808,0x3d83db0a,0x3f7de0b1,0x3e039502,0x3f7d1cdd,0x3e195be0,0x3f7a1e84,0x3e5a3997,0x3f78e3d6,0x3e6fa8b2,
0x3f748422,0x3e97a117,0x3f72d4eb,0x3ea21887,0x3f7fb10f,0x3d48fb30,0x3f7f4e6d,0x3d96a905,0x3f7d3aac,0x3e164083,0x3f7c3b28,0x3e2f10a2,
0x3f7853f8,0x3e78cfcc,0x3f76ba07,0x3e888e93,0x3f710908,0x3eac7cd4,0x3f6ed89e,0x3eb8442a,0x3f7f9c18,0x3d621469,0x3f7f1f49,0x3da973ba,
0x3f7c7eb0,0x3e28defc,0x3f7b3bab,0x3e44b0b9,0x3f764d97,0x3e8b9507,0x3f74484b,0x3e9920fe,0x3f6d1c1d,0x3ec1071e,0x3f6a5ad9,0x3ece0bea,
0x3f7f84ab,0x3d7b2b74,0x3f7eea9d,0x3dbc3ac3,0x3f7baccd,0x3e3b6ecf,0x3f7a1e84,0x3e5a3997,0x3f740bdd,0x3e9aa086,0x3f718f57,0x3ea986c4,
0x3f68bf3c,0x3ed53641,0x3f655e0b,0x3ee363fa,0x3f7f6ac7,0x3d8a200a,0x3f7eb069,0x3dcefdb7,0x3f7ac516,0x3e4dee60,0x3f78e3d6,0x3e6fa8b2,
0x3f718f57,0x3ea986c4,0x3f6e8ff8,0x3eb9bb1e,0x3f63f473,0x3ee900b7,0x3f5fe4e9,0x3ef840c8,0x3f7f4e6d,0x3d96a905,0x3f7e70b0,0x3de1bc2e,
0x3f79c79d,0x3e605c13,0x3f778bc5,0x3e827dc0,0x3f6ed89e,0x3eb8442a,0x3f6b4b0c,0x3ec9b953,0x3f5ebe05,0x3efc5d27,0x3f59f26a,0x3f064b82,
0x3f7f2f9d,0x3da3308c,0x3f7e2b72,0x3df475c0,0x3f78b47b,0x3e72b651,0x3f76167a,0x3e8d17c0,0x3f6be858,0x3ec6d529,0x3f67c187,0x3ed97cb9,
0x3f591e6a,0x3f07a136,0x3f5389c7,0x3f102dd5,0x3f7f0e58,0x3dafb680,0x3f7de0b1,0x3e039502,0x3f778bc5,0x3e827dc0,0x3f748422,0x3e97a117,
0x3f68bf3c,0x3ed53641,0x3f63f473,0x3ee900b7,0x3f531849,0x3f10d3cd,0x3f4cae79,0x3f19c200,0x3f7eea9d,0x3dbc3ac3,0x3f7d906e,0x3e0cec4a,
0x3f764d97,0x3e8b9507,0x3f72d4eb,0x3ea21887,0x3f655e0b,0x3ee363fa,0x3f5fe4e9,0x3ef840c8,0x3f4cae79,0x3f19c200,0x3f456439,0x3f2302d3,
0x3f7ec46d,0x3dc8bd36,0x3f7d3aac,0x3e164083,0x3f74fa0b,0x3e94a031,0x3f710908,0x3eac7cd4,0x3f61c598,0x3ef15aea,0x3f5b941a,0x3f039c3d,
0x3f45e403,0x3f226799,0x3f3daef9,0x3f2beb4a,0x3f7e9bc9,0x3dd53db9,0x3f7cdf6c,0x3e1f917b,0x3f73913f,0x3e9d9e78,0x3f6f20b0,0x3eb6ccc3,
0x3f5df6be,0x3eff17b2,0x3f570348,0x3f0af1b7,0x3f3ebc1b,0x3f2ac082,0x3f3592e7,0x3f34768f,0x3f7e70b0,0x3de1bc2e,0x3f7c7eb0,0x3e28defc,
0x3f721352,0x3ea68f12,0x3f6d1c1d,0x3ec1071e,0x3f59f26a,0x3f064b82,0x3f5233c6,0x3f121eb0,0x3f373a23,0x3f32c8c9,0x3f2d1469,0x3f3ca003,
0x3f7e4323,0x3dee3876,0x3f7c187a,0x3e3228d4,0x3f708066,0x3eaf713a,0x3f6afb8c,0x3ecb2aae,0x3f55b993,0x3f0cead0,0x3f4d26fd,0x3f19210f,
0x3f2f61a5,0x3f3a7ca4,0x3f24381a,0x3f446337,0x3f7e1324,0x3dfab273,0x3f7baccd,0x3e3b6ecf,0x3f6ed89e,0x3eb8442a,0x3f68bf3c,0x3ed53641,
0x3f514d3d,0x3f13682a,0x3f47de65,0x3f1ff6cb,0x3f273656,0x3f41d870,0x3f1b02c6,0x3f4bbbf8,0x3f7de0b1,0x3e039502,0x3f7b3bab,0x3e44b0b9,
0x3f6d1c1d,0x3ec1071e,0x3f666771,0x3edf28a9,0x3f4cae79,0x3f19c200,0x3f425b89,0x3f269de3,0x3f1ebc12,0x3f48d8b3,0x3f11796b,0x3f52a649,
0x3f7dabcc,0x3e09cf86,0x3f7ac516,0x3e4dee60,0x3f6b4b0c,0x3ec9b953,0x3f63f473,0x3ee900b7,0x3f47de65,0x3f1ff6cb,0x3f3ca003,0x3f2d1469,
0x3f15f6d9,0x3f4f7a1f,0x3f07a136,0x3f591e6a,0x3f7d7474,0x3e1008b7,0x3f7a4910,0x3e57278f,0x3f696591,0x3ed25a09,0x3f61668a,0x3ef2bd43,
0x3f42de29,0x3f26050a,0x3f36ad7f,0x3f33587a,0x3f0cead0,0x3f55b993,0x3efafef7,0x3f5f20db,0x3f7d3aac,0x3e164083,0x3f79c79d,0x3e605c13,
0x3f676bd8,0x3edae880,0x3f5ebe05,0x3efc5d27,0x3f3daef9,0x3f2beb4a,0x3f3085bb,0x3f396842,0x3f039c3d,0x3f5b941a,0x3ee63375,0x3f64aa59,
0x3f7cfe73,0x3e1c76de,0x3f7940c0,0x3e698bba,0x3f655e0b,0x3ee363fa,0x3f5bfb34,0x3f02ef9f,0x3f385216,0x3f31a81d,0x3f2a2a80,0x3f3f41fc,
0x3ef41f07,0x3f6106f2,0x3ed0eb2a,0x3f69b7e4,0x3f7cbfc9,0x3e22abb6,0x3f78b47b,0x3e72b651,0x3f633c5a,0x3eebcbbb,0x3f591e6a,0x3f07a136,
0x3f32c8c9,0x3f373a23,0x3f239da9,0x3f44e3f5,0x3ee0924f,0x3f660f88,0x3ebb31a0,0x3f6e46be,0x3f7c7eb0,0x3e28defc,0x3f7822d1,0x3e7bdba4,
0x3f6106f2,0x3ef41f07,0x3f5627fe,0x3f0c42c9,0x3f2d1469,0x3f3ca003,0x3f1ce11f,0x3f4a4c87,0x3ecc9b8b,0x3f6aab7b,0x3ea5129f,0x3f725470,
0x3f7c3b28,0x3e2f10a2,0x3f778bc5,0x3e827dc0,0x3f5ebe05,0x3efc5d27,0x3f531849,0x3f10d3cd,0x3f273656,0x3f41d870,0x3f15f6d9,0x3f4f7a1f,
0x3eb8442a,0x3f6ed89e,0x3e8e9a22,0x3f75dec6,0x3f7bf531,0x3e354098,0x3f76ef5b,0x3e870ada,0x3f5c61c7,0x3f0242b1,0x3f4fefa8,0x3f1553b7,
0x3f212ff9,0x3f46e22a,0x3f0ee0db,0x3f546b3b,0x3ea395c5,0x3f7294f8,0x3e6fa8b2,0x3f78e3d6,0x3f7baccd,0x3e3b6ecf,0x3f764d97,0x3e8b9507,
0x3f59f26a,0x3f064b82,0x3f4cae79,0x3f19c200,0x3f1b02c6,0x3f4bbbf8,0x3f07a136,0x3f591e6a,0x3e8e9a22,0x3f75dec6,0x3e419b37,0x3f7b61fc,
0x3f7b61fc,0x3e419b37,0x3f75a67b,0x3e901c2c,0x3f577026,0x3f0a48ad,0x3f495521,0x3f1e1e22,0x3f14b039,0x3f5064af,0x3f003a06,0x3f5d924d,
0x3e72b651,0x3f78b47b,0x3e1324ca,0x3f7d57de,0x3f800000,0,0x3f800000,0,0x3f800000,0,0x3f800000,0,
0x3f800000,0,0x3f800000,0,0x3f800000,0,0x3f800000,0,0x3f7fb10f,0x3d48fb30,0x3f7fa6e3,0x3d55880e,
0x3f7f84ab,0x3d7b2b74,0x3f7f7808,0x3d83db0a,0x3f7f4e6d,0x3d96a905,0x3f7f3f54,0x3d9cecf9,0x3f7f0e58,0x3dafb680,0x3f7efcc9,0x3db5f8da,
0x3f7ec46d,0x3dc8bd36,0x3f7e9bc9,0x3dd53db9,0x3f7e1324,0x3dfab273,0x3f7de0b1,0x3e039502,0x3f7d3aac,0x3e164083,0x3f7cfe73,0x3e1c76de,
0x3f7c3b28,0x3e2f10a2,0x3f7bf531,0x3e354098,0x3f7d3aac,0x3e164083,0x3f7cdf6c,0x3e1f917b,0x3f7baccd,0x3e3b6ecf,0x3f7b3bab,0x3e44b0b9,
0x3f79c79d,0x3e605c13,0x3f7940c0,0x3e698bba,0x3f778bc5,0x3e827dc0,0x3f76ef5b,0x3e870ada,0x3f7b14be,0x3e47c5c2,0x3f7a7302,0x3e541501,
0x3f7853f8,0x3e78cfcc,0x3f778bc5,0x3e827dc0,0x3f74fa0b,0x3e94a031,0x3f740bdd,0x3e9aa086,0x3f710908,0x3eac7cd4,0x3f6ff573,0x3eb263ef,
0x3f7853f8,0x3e78cfcc,0x3f77583a,0x3e840270,0x3f740bdd,0x3e9aa086,0x3f72d4eb,0x3ea21887,0x3f6ed89e,0x3eb8442a,0x3f6d67a1,0x3ebf926f,
0x3f68bf3c,0x3ed53641,0x3f671599,0x3edc53c1,0x3f74fa0b,0x3e94a031,0x3f73913f,0x3e9d9e78,0x3f6ed89e,0x3eb8442a,0x3f6d1c1d,0x3ec1071e,
0x3f676bd8,0x3edae880,0x3f655e0b,0x3ee363fa,0x3f5ebe05,0x3efc5d27,0x3f5c61c7,0x3f0242b1,0x3f710908,0x3eac7cd4,0x3f6f20b0,0x3eb6ccc3,
0x3f68bf3c,0x3ed53641,0x3f666771,0x3edf28a9,0x3f5ebe05,0x3efc5d27,0x3f5bfb34,0x3f02ef9f,0x3f531849,0x3f10d3cd,0x3f4fefa8,0x3f1553b7,
0x3f6c835e,0x3ec3ef15,0x3f6a09a7,0x3ecf7bca,0x3f61c598,0x3ef15aea,0x3f5ebe05,0x3efc5d27,0x3f54db31,0x3f0e39da,0x3f514d3d,0x3f13682a,
0x3f45e403,0x3f226799,0x3f41d870,0x3f273656,0x3f676bd8,0x3edae880,0x3f644fac,0x3ee79a5d,0x3f59f26a,0x3f064b82,0x3f5627fe,0x3f0c42c9,
0x3f49d112,0x3f1d7fd1,0x3f456439,0x3f2302d3,0x3f373a23,0x3f32c8c9,0x3f3238aa,0x3f37c655,0x3f61c598,0x3ef15aea,0x3f5df6be,0x3eff17b2,
0x3f514d3d,0x3f13682a,0x3f4cae79,0x3f19c200,0x3f3daef9,0x3f2beb4a,0x3f385216,0x3f31a81d,0x3f273656,0x3f41d870,0x3f212ff9,0x3f46e22a,
0x3f5b941a,0x3f039c3d,0x3f570348,0x3f0af1b7,0x3f47de65,0x3f1ff6cb,0x3f425b89,0x3f269de3,0x3f3085bb,0x3f396842,0x3f2a2a80,0x3f3f41fc,
0x3f15f6d9,0x3f4f7a1f,0x3f0ee0db,0x3f546b3b,0x3f54db31,0x3f0e39da,0x3f4f7a1f,0x3f15f6d9,0x3f3daef9,0x3f2beb4a,0x3f373a23,0x3f32c8c9,
0x3f226799,0x3f45e403,0x3f1b02c6,0x3f4bbbf8,0x3f039c3d,0x3f5b941a,0x3ef6e0cb,0x3f604621,0x3f4d9f02,0x3f187fc0,0x3f476085,0x3f209393,
0x3f32c8c9,0x3f373a23,0x3f2b561b,0x3f3e35c5,0x3f13682a,0x3f514d3d,0x3f0af1b7,0x3f570348,0x3ee0924f,0x3f660f88,0x3ece0bea,0x3f6a5ad9,
0x3f45e403,0x3f226799,0x3f3ebc1b,0x3f2ac082,0x3f273656,0x3f41d870,0x3f1ebc12,0x3f48d8b3,0x3f039c3d,0x3f5b941a,0x3ef41f07,0x3f6106f2,
0x3eb8442a,0x3f6ed89e,0x3ea395c5,0x3f7294f8,0x3f3daef9,0x3f2beb4a,0x3f3592e7,0x3f34768f,0x3f1b02c6,0x3f4bbbf8,0x3f11796b,0x3f52a649,
0x3ee63375,0x3f64aa59,0x3ed0eb2a,0x3f69b7e4,0x3e8e9a22,0x3f75dec6,0x3e6fa8b2,0x3f78e3d6,0x3f3504f3,0x3f3504f3,0x3f2beb4a,0x3f3daef9,
0x3f0e39da,0x3f54db31,0x3f039c3d,0x3f5b941a,0x3ec3ef15,0x3f6c835e,0x3eac7cd4,0x3f710908,0x3e47c5c2,0x3f7b14be,0x3e164083,0x3f7d3aac,
0x3f2beb4a,0x3f3daef9,0x3f21cbfb,0x3f466354,0x3f00e7e4,0x3f5d2d53,0x3eea6681,0x3f6398ac,0x3ea09ae5,0x3f731447,0x3e870ada,0x3f76ef5b,
0x3de1bc2e,0x3f7e70b0,0x3d6ea038,0x3f7f90b1,0x3f226799,0x3f45e403,0x3f173c07,0x3f4e8d90,0x3ee63375,0x3f64aa59,0x3ecc9b8b,0x3f6aab7b,
0x3e78cfcc,0x3f7853f8,0x3e419b37,0x3f7b61fc,0x3cc90ab0,0x3f7fec43,0xbcfb49ba,0x3f7fe129,0x3f187fc0,0x3f4d9f02,0x3f0c42c9,0x3f5627fe,
0x3ec9b953,0x3f6b4b0c,0x3eadf73c,0x3f70c501,0x3e2f10a2,0x3f7c3b28,0x3de7fa9a,0x3f7e5a38,0xbd7b2b74,0x3f7f84ab,0xbdf475c0,0x3f7e2b72,
0x3f0e39da,0x3f54db31,0x3f00e7e4,0x3f5d2d53,0x3eac7cd4,0x3f710908,0x3e8e9a22,0x3f75dec6,0x3dc8bd36,0x3f7ec46d,0x3d16c32c,0x3f7fd397,
0xbe164083,0x3f7d3aac,0xbe541501,0x3f7a7302,0x3f039c3d,0x3f5b941a,0x3eea6681,0x3f6398ac,0x3e8e9a22,0x3f75dec6,0x3e5d4b1a,0x3f79f35e,
0x3cc90ab0,0x3f7fec43,0xbd2351cb,0x3f7fcbe2,0xbe6c9a7f,0x3f791298,0xbe9620d2,0x3f74bf62,0x3ef15aea,0x3f61c598,0x3ed25a09,0x3f696591,
0x3e605c13,0x3f79c79d,0x3e1c76de,0x3f7cfe73,0xbd48fb30,0x3f7fb10f,0xbdee3876,0x3f7e4323,0xbea09ae5,0x3f731447,0xbec1071e,0x3f6d1c1d,
0x3edae880,0x3f676bd8,0x3eb9bb1e,0x3f6e8ff8,0x3e22abb6,0x3f7cbfc9,0x3db5f8da,0x3f7efcc9,0xbdfab273,0x3f7e1324,0xbe44b0b9,0x3f7b3bab,
0xbec9b953,0x3f6b4b0c,0xbeea6681,0x3f6398ac,0x3ec3ef15,0x3f6c835e,0x3ea09ae5,0x3f731447,0x3dc8bd36,0x3f7ec46d,0x3cc90ab0,0x3f7fec43,
0xbe47c5c2,0x3f7b14be,0xbe888e93,0x3f76ba07,0xbef15aea,0x3f61c598,0xbf08f59b,0x3f584853,0x3eac7cd4,0x3f710908,0x3e870ada,0x3f76ef5b,
0x3d16c32c,0x3f7fd397,0xbd2351cb,0x3f7fcbe2,0xbe888e93,0x3f76ba07,0xbeadf73c,0x3f70c501,0xbf0b9a6b,0x3f5695e5,0xbf1ba299,0x3f4b41fa,
0x3e94a031,0x3f74fa0b,0x3e5a3997,0x3f7a1e84,0xbcc90ab0,0x3f7fec43,0xbdd53db9,0x3f7e9bc9,0xbeac7cd4,0x3f710908,0xbed25a09,0x3f696591,
0xbf1d7fd1,0x3f49d112,0xbf2d1469,0x3f3ca003,0x3e78cfcc,0x3f7853f8,0x3e25c58c,0x3f7c9f8a,0xbdafb680,0x3f7f0e58,0xbe2bf804,0x3f7c5d3a,
0xbecf7bca,0x3f6a09a7,0xbef58035,0x3f60a6cf,0xbf2e3bde,0x3f3b8f3b,0xbf3d27b8,0x3f2c800f,0x3e47c5c2,0x3f7b14be,0x3de1bc2e,0x3f7e70b0,
0xbe164083,0x3f7d3aac,0xbe6c9a7f,0x3f791298,0xbef15aea,0x3f61c598,0xbf0b9a6b,0x3f5695e5,0xbf3daef9,0x3f2beb4a,0xbf4bbbf8,0x3f1b02c6,
0x3e164083,0x3f7d3aac,0x3d6ea038,0x3f7f90b1,0xbe541501,0x3f7a7302,0xbe9620d2,0x3f74bf62,0xbf08f59b,0x3f584853,0xbf1ba299,0x3f4b41fa,
0xbf4bbbf8,0x3f1b02c6,0xbf58b3a1,0x3f084b92,0x3dc8bd36,0x3f7ec46d,0x3bc90f88,0x3f7ffec4,0xbe888e93,0x3f76ba07,0xbeb554ec,0x3f6f6830,
0xbf187fc0,0x3f4d9f02,0xbf2ac082,0x3f3ebc1b,0xbf584853,0x3f08f59b,0xbf63f473,0x3ee900b7,0x3d48fb30,0x3f7fb10f,0xbd3c6dd5,0x3f7fba9e,
0xbea68f12,0x3f721352,0xbed3c867,0x3f6912ae,0xbf273656,0x3f41d870,0xbf38dd65,0x3f311722,0xbf633c5a,0x3eebcbbb,0xbf6d67a1,0x3ebf926f,
0x3f800000,0,0x3f800000,0,0x3f800000,0,0x3f800000,0,0x3f800000,0,0x3f800000,0,
0x3f800000,0,0x3f800000,0,0x3f7f9c18,0x3d621469,0x3f7f90b1,0x3d6ea038,0x3f7f6ac7,0x3d8a200a,0x3f7f5ce9,0x3d9064b4,
0x3f7f2f9d,0x3da3308c,0x3f7f1f49,0x3da973ba,0x3f7eea9d,0x3dbc3ac3,0x3f7ed7d4,0x3dc27c39,0x3f7e70b0,0x3de1bc2e,0x3f7e4323,0x3dee3876,
0x3f7dabcc,0x3e09cf86,0x3f7d7474,0x3e1008b7,0x3f7cbfc9,0x3e22abb6,0x3f7c7eb0,0x3e28defc,0x3f7baccd,0x3e3b6ecf,0x3f7b61fc,0x3e419b37,
0x3f7c7eb0,0x3e28defc,0x3f7c187a,0x3e3228d4,0x3f7ac516,0x3e4dee60,0x3f7a4910,0x3e57278f,0x3f78b47b,0x3e72b651,0x3f7822d1,0x3e7bdba4,
0x3f764d97,0x3e8b9507,0x3f75a67b,0x3e901c2c,0x3f79c79d,0x3e605c13,0x3f791298,0x3e6c9a7f,0x3f76ba07,0x3e888e93,0x3f75dec6,0x3e8e9a22,
0x3f731447,0x3ea09ae5,0x3f721352,0x3ea68f12,0x3f6ed89e,0x3eb8442a,0x3f6db293,0x3ebe1d4a,0x3f764d97,0x3e8b9507,0x3f75341d,0x3e931f35,
0x3f718f57,0x3ea986c4,0x3f703b37,0x3eb0eacb,0x3f6be858,0x3ec6d529,0x3f6a5ad9,0x3ece0bea,0x3f655e0b,0x3ee363fa,0x3f6398ac,0x3eea6681,
0x3f721352,0x3ea68f12,0x3f708066,0x3eaf713a,0x3f6b4b0c,0x3ec9b953,0x3f696591,0x3ed25a09,0x3f633c5a,0x3eebcbbb,0x3f6106f2,0x3ef41f07,
0x3f59f26a,0x3f064b82,0x3f577026,0x3f0a48ad,0x3f6d1c1d,0x3ec1071e,0x3f6afb8c,0x3ecb2aae,0x3f63f473,0x3ee900b7,0x3f61668a,0x3ef2bd43,
0x3f591e6a,0x3f07a136,0x3f5627fe,0x3f0c42c9,0x3f4cae79,0x3f19c200,0x3f495521,0x3f1e1e22,0x3f676bd8,0x3edae880,0x3f64aa59,0x3ee63375,
0x3f5b941a,0x3f039c3d,0x3f584853,0x3f08f59b,0x3f4d9f02,0x3f187fc0,0x3f49d112,0x3f1d7fd1,0x3f3daef9,0x3f2beb4a,0x3f396842,0x3f3085bb,
0x3f6106f2,0x3ef41f07,0x3f5d924d,0x3f003a06,0x3f5233c6,0x3f121eb0,0x3f4e1689,0x3f17de12,0x3f40d0da,0x3f286605,0x3f3c17d9,0x3f2da859,
0x3f2d1469,0x3f3ca003,0x3f27ce61,0x3f4154e1,0x3f59f26a,0x3f064b82,0x3f55b993,0x3f0cead0,0x3f47de65,0x3f1ff6cb,0x3f42de29,0x3f26050a,
0x3f32c8c9,0x3f373a23,0x3f2d1469,0x3f3ca003,0x3f1b02c6,0x3f4bbbf8,0x3f14b039,0x3f5064af,0x3f5233c6,0x3f121eb0,0x3f4d26fd,0x3f19210f,
0x3f3ca003,0x3f2d1469,0x3f36ad7f,0x3f33587a,0x3f239da9,0x3f44e3f5,0x3f1ce11f,0x3f4a4c87,0x3f07a136,0x3f591e6a,0x3f003a06,0x3f5d924d,
0x3f49d112,0x3f1d7fd1,0x3f43e200,0x3f24d225,0x3f3085bb,0x3f396842,0x3f299415,0x3f3fc767,0x3f13682a,0x3f514d3d,0x3f0b9a6b,0x3f5695e5,
0x3ee63375,0x3f64aa59,0x3ed53641,0x3f68bf3c,0x3f40d0da,0x3f286605,0x3f39f2ac,0x3f2ff3e6,0x3f239da9,0x3f44e3f5,0x3f1ba299,0x3f4b41fa,
0x3f0242b1,0x3f5c61c7,0x3ef2bd43,0x3f61668a,0x3ebb31a0,0x3f6e46be,0x3ea80b1f,0x3f71d19f,0x3f373a23,0x3f32c8c9,0x3f2f61a5,0x3f3a7ca4,
0x3f15f6d9,0x3f4f7a1f,0x3f0cead0,0x3f55b993,0x3ee0924f,0x3f660f88,0x3ecc9b8b,0x3f6aab7b,0x3e8e9a22,0x3f75dec6,0x3e72b651,0x3f78b47b,
0x3f2d1469,0x3f3ca003,0x3f24381a,0x3f446337,0x3f07a136,0x3f591e6a,0x3efafef7,0x3f5f20db,0x3ebb31a0,0x3f6e46be,0x3ea5129f,0x3f725470,
0x3e419b37,0x3f7b61fc,0x3e1324ca,0x3f7d57de,0x3f226799,0x3f45e403,0x3f187fc0,0x3f4d9f02,0x3ef15aea,0x3f61c598,0x3edae880,0x3f676bd8,
0x3e94a031,0x3f74fa0b,0x3e78cfcc,0x3f7853f8,0x3dc8bd36,0x3f7ec46d,0x3d48fb30,0x3f7fb10f,0x3f173c07,0x3f4e8d90,0x3f0c42c9,0x3f5627fe,
0x3ed25a09,0x3f696591,0x3eb9bb1e,0x3f6e8ff8,0x3e5a3997,0x3f7a1e84,0x3e25c58c,0x3f7c9f8a,0x3bc90f88,0x3f7ffec4,0xbd3c6dd5,0x3f7fba9e,
0x3f0b9a6b,0x3f5695e5,0x3eff17b2,0x3f5df6be,0x3eb263ef,0x3f6ff573,0x3e97a117,0x3f748422,0x3e09cf86,0x3f7dabcc,0x3da3308c,0x3f7f2f9d,
0xbdafb680,0x3f7f0e58,0xbe1008b7,0x3f7d7474,0x3eff17b2,0x3f5df6be,0x3ee4cbfe,0x3f650479,0x3e919ddd,0x3f756d97,0x3e698bba,0x3f7940c0,
0x3d621469,0x3f7f9c18,0xbb490fc6,0x3f7fffb1,0xbe354098,0x3f7bf531,0xbe6fa8b2,0x3f78e3d6,0x3ee63375,0x3f64aa59,0x3ec9b953,0x3f6b4b0c,
0x3e605c13,0x3f79c79d,0x3e22abb6,0x3f7cbfc9,0xbcc90ab0,0x3f7fec43,0xbdafb680,0x3f7f0e58,0xbe888e93,0x3f76ba07,0xbea68f12,0x3f721352,
0x3ecc9b8b,0x3f6aab7b,0x3eadf73c,0x3f70c501,0x3e1c76de,0x3f7cfe73,0x3db5f8da,0x3f7efcc9,0xbdd53db9,0x3f7e9bc9,0xbe2bf804,0x3f7c5d3a,
0xbeb554ec,0x3f6f6830,0xbed3c867,0x3f6912ae,0x3eb263ef,0x3f6ff573,0x3e919ddd,0x3f756d97,0x3dafb680,0x3f7f0e58,0x3c96c9b6,0x3f7ff4e6,
0xbe3b6ecf,0x3f7baccd,0xbe7ee6e1,0x3f77f110,0xbee0924f,0x3f660f88,0xbeff17b2,0x3f5df6be,0x3e97a117,0x3f748422,0x3e698bba,0x3f7940c0,
0x3c96c9b6,0x3f7ff4e6,0xbd55880e,0x3f7fa6e3,0xbe8586ce,0x3f772417,0xbea80b1f,0x3f71d19f,0xbf04f484,0x3f5ac450,0xbf140c5f,0x3f50d937,
0x3e78cfcc,0x3f7853f8,0x3e2f10a2,0x3f7c3b28,0xbd48fb30,0x3f7fb10f,0xbdfab273,0x3f7e1324,0xbeac7cd4,0x3f710908,0xbecf7bca,0x3f6a09a7,
0xbf187fc0,0x3f4d9f02,0xbf273656,0x3f41d870,0x3e419b37,0x3f7b61fc,0x3de7fa9a,0x3f7e5a38,0xbdee3876,0x3f7e4323,0xbe44b0b9,0x3f7b3bab,
0xbed25a09,0x3f696591,0xbef58035,0x3f60a6cf,0xbf2ac082,0x3f3ebc1b,0xbf38dd65,0x3f311722,0x3e09cf86,0x3f7dabcc,0x3d621469,0x3f7f9c18,
0xbe3b6ecf,0x3f7baccd,0xbe8586ce,0x3f772417,0xbef6e0cb,0x3f604621,0xbf0cead0,0x3f55b993,0xbf3b8f3b,0x3f2e3bde,0xbf48d8b3,0x3f1ebc12,
0x3da3308c,0x3f7f2f9d,0xbb490fc6,0x3f7fffb1,0xbe7ee6e1,0x3f77f110,0xbea80b1f,0x3f71d19f,0xbf0cead0,0x3f55b993,0xbf1e1e22,0x3f495521,
0xbf4ac77f,0x3f1c420c,0xbf570348,0x3f0af1b7,0x3cc90ab0,0x3f7fec43,0xbd7b2b74,0x3f7f84ab,0xbea09ae5,0x3f731447,0xbec9b953,0x3f6b4b0c,
0xbf1d7fd1,0x3f49d112,0xbf2e3bde,0x3f3b8f3b,0xbf584853,0x3f08f59b,0xbf633c5a,0x3eebcbbb,0xbcfb49ba,0x3f7fe129,0xbdf475c0,0x3f7e2b72,
0xbec1071e,0x3f6d1c1d,0xbeea6681,0x3f6398ac,0xbf2d1469,0x3f3ca003,0xbf3d27b8,0x3f2c800f,0xbf63f473,0x3ee900b7,0xbf6d67a1,0x3ebf926f,
0xbdafb680,0x3f7f0e58,0xbe354098,0x3f7bf531,0xbee0924f,0x3f660f88,0xbf04f484,0x3f5ac450,0xbf3b8f3b,0x3f2e3bde,0xbf4ac77f,0x3f1c420c,
0xbf6db293,0x3ebe1d4a,0xbf756d97,0x3e919ddd,0xbe1008b7,0x3f7d7474,0xbe6fa8b2,0x3f78e3d6,0xbeff17b2,0x3f5df6be,0xbf140c5f,0x3f50d937,
0xbf48d8b3,0x3f1ebc12,0xbf570348,0x3f0af1b7,0xbf756d97,0x3e919ddd,0xbf7b3bab,0x3e44b0b9,0x3f800000,0,0x3f800000,0,
0x3f800000,0,0x3f800000,0,0x3f800000,0,0x3f800000,0,0x3f800000,0,0x3f800000,0,
0x3f7ec46d,0x3dc8bd36,0x3f7eb069,0x3dcefdb7,0x3f7e70b0,0x3de1bc2e,0x3f7e5a38,0x3de7fa9a,0x3f7e1324,0x3dfab273,0x3f7dfa38,0x3e007745,
0x3f7dabcc,0x3e09cf86,0x3f7d906e,0x3e0cec4a,0x3f7b14be,0x3e47c5c2,0x3f7ac516,0x3e4dee60,0x3f79c79d,0x3e605c13,0x3f796e4e,0x3e667c66,
0x3f7853f8,0x3e78cfcc,0x3f77f110,0x3e7ee6e1,0x3f76ba07,0x3e888e93,0x3f764d97,0x3e8b9507,0x3f74fa0b,0x3e94a031,0x3f74484b,0x3e9920fe,
0x3f721352,0x3ea68f12,0x3f714c7a,0x3eab0201,0x3f6ed89e,0x3eb8442a,0x3f6dfcf2,0x3ebca7af,0x3f6b4b0c,0x3ec9b953,0x3f6a5ad9,0x3ece0bea,
0x3f6c835e,0x3ec3ef15,0x3f6b4b0c,0x3ec9b953,0x3f676bd8,0x3edae880,0x3f660f88,0x3ee0924f,0x3f61c598,0x3ef15aea,0x3f604621,0x3ef6e0cb,
0x3f5b941a,0x3f039c3d,0x3f59f26a,0x3f064b82,0x3f61c598,0x3ef15aea,0x3f5fe4e9,0x3ef840c8,0x3f59f26a,0x3f064b82,0x3f57dc7f,0x3f099f4e,
0x3f514d3d,0x3f13682a,0x3f4f0417,0x3f16999f,0x3f47de65,0x3f1ff6cb,0x3f456439,0x3f2302d3,0x3f54db31,0x3f0e39da,0x3f5233c6,0x3f121eb0,
0x3f49d112,0x3f1d7fd1,0x3f46e22a,0x3f212ff9,0x3f3daef9,0x3f2beb4a,0x3f3a7ca4,0x3f2f61a5,0x3f3085bb,0x3f396842,0x3f2d1469,0x3f3ca003,
0x3f45e403,0x3f226799,0x3f425b89,0x3f269de3,0x3f373a23,0x3f32c8c9,0x3f33587a,0x3f36ad7f,0x3f273656,0x3f41d870,0x3f2302d3,0x3f456439,
0x3f15f6d9,0x3f4f7a1f,0x3f11796b,0x3f52a649,0x3f3504f3,0x3f3504f3,0x3f3085bb,0x3f396842,0x3f226799,0x3f45e403,0x3f1d7fd1,0x3f49d112,
0x3f0e39da,0x3f54db31,0x3f08f59b,0x3f584853,0x3ef15aea,0x3f61c598,0x3ee63375,0x3f64aa59,0x3f226799,0x3f45e403,0x3f1ce11f,0x3f4a4c87,
0x3f0b9a6b,0x3f5695e5,0x3f05a02c,0x3f5a5ba0,0x3ee63375,0x3f64aa59,0x3ed97cb9,0x3f67c187,0x3eb263ef,0x3f6ff573,0x3ea5129f,0x3f725470,
0x3f0e39da,0x3f54db31,0x3f07a136,0x3f591e6a,0x3ee63375,0x3f64aa59,0x3ed8106b,0x3f6816a8,0x3eac7cd4,0x3f710908,0x3e9d9e78,0x3f73913f,
0x3e605c13,0x3f79c79d,0x3e419b37,0x3f7b61fc,0x3ef15aea,0x3f61c598,0x3ee1fb6a,0x3f65b710,0x3eb263ef,0x3f6ff573,0x3ea21887,0x3f72d4eb,
0x3e605c13,0x3f79c79d,0x3e3e853e,0x3f7b87b2,0x3dafb680,0x3f7f0e58,0x3d55880e,0x3f7fa6e3,0x3ec3ef15,0x3f6c835e,0x3eb263ef,0x3f6ff573,
0x3e78cfcc,0x3f7853f8,0x3e541501,0x3f7a7302,0x3dc8bd36,0x3f7ec46d,0x3d7b2b74,0x3f7f84ab,0xbd48fb30,0x3f7fb10f,0xbdafb680,0x3f7f0e58,
0x3e94a031,0x3f74fa0b,0x3e80f8c0,0x3f77beb7,0x3e09cf86,0x3f7dabcc,0x3dc27c39,0x3f7ed7d4,0xbcc90ab0,0x3f7fec43,0xbd83db0a,0x3f7f7808,
0xbe3b6ecf,0x3f7baccd,0xbe636c83,0x3f799b43,0x3e47c5c2,0x3f7b14be,0x3e1c76de,0x3f7cfe73,0x3cc90ab0,0x3f7fec43,0xbc96c9b6,0x3f7ff4e6,
0xbe164083,0x3f7d3aac,0xbe419b37,0x3f7b61fc,0xbea09ae5,0x3f731447,0xbeb554ec,0x3f6f6830,0x3dc8bd36,0x3f7ec46d,0x3d55880e,0x3f7fa6e3,
0xbdafb680,0x3f7f0e58,0xbe06b26e,0x3f7dc68c,0xbe888e93,0x3f76ba07,0xbe9f1cdf,0x3f73530e,0xbee0924f,0x3f660f88,0xbef58035,0x3f60a6cf,
0x248d3132,0x3f800000,0xbd48fb30,0x3f7fb10f,0xbe47c5c2,0x3f7b14be,0xbe78cfcc,0x3f7853f8,0xbec3ef15,0x3f6c835e,0xbedae880,0x3f676bd8,
0xbf0e39da,0x3f54db31,0xbf187fc0,0x3f4d9f02,0xbdc8bd36,0x3f7ec46d,0xbe195be0,0x3f7d1cdd,0xbe9aa086,0x3f740bdd,0xbeb3dca5,0x3f6faf1b,
0xbefc5d27,0x3f5ebe05,0xbf099f4e,0x3f57dc7f,0xbf299415,0x3f3fc767,0xbf33587a,0x3f36ad7f,0xbe47c5c2,0x3f7b14be,0xbe7ee6e1,0x3f77f110,
0xbecf7bca,0x3f6a09a7,0xbee900b7,0x3f63f473,0xbf187fc0,0x3f4d9f02,0xbf239da9,0x3f44e3f5,0xbf41d870,0x3f273656,0xbf4ac77f,0x3f1c420c,
0xbe94a031,0x3f74fa0b,0xbeb0eacb,0x3f703b37,0xbf00e7e4,0x3f5d2d53,0xbf0d9281,0x3f554aa4,0xbf3085bb,0x3f396842,0xbf3b0629,0x3f2ecef7,
0xbf5695e5,0x3f0b9a6b,0xbf5e5aa6,0x3efdbabb,0xbec3ef15,0x3f6c835e,0xbee0924f,0x3f660f88,0xbf187fc0,0x3f4d9f02,0xbf24d225,0x3f43e200,
0xbf45e403,0x3f226799,0xbf4f7a1f,0x3f15f6d9,0xbf676bd8,0x3edae880,0xbf6db293,0x3ebe1d4a,0xbef15aea,0x3f61c598,0xbf06f686,0x3f5988ad,
0xbf2e3bde,0x3f3b8f3b,0xbf39f2ac,0x3f2ff3e6,0xbf584853,0x3f08f59b,0xbf60a6cf,0x3ef58035,0xbf740bdd,0x3e9aa086,0xbf788486,0x3e75c35a,
0xbf0e39da,0x3f54db31,0xbf1c420c,0x3f4ac77f,0xbf41d870,0x3f273656,0xbf4cae79,0x3f19c200,0xbf676bd8,0x3edae880,0xbf6e46be,0x3ebb31a0,
0xbf7c3b28,0x3e2f10a2,0xbf7e9bc9,0x3dd53db9,0xbf226799,0x3f45e403,0xbf2ff3e6,0x3f39f2ac,0xbf531849,0x3f10d3cd,0xbf5cc7d1,0x3f019573,
0xbf731447,0x3ea09ae5,0xbf7822d1,0x3e7bdba4,0xbf7fd397,0x3d16c32c,0xbf7fdaaf,0xbd0a342f,0xbf3504f3,0x3f3504f3,0xbf41d870,0x3f273656,
0xbf61c598,0x3ef15aea,0xbf6a09a7,0x3ecf7bca,0xbf7b14be,0x3e47c5c2,0xbf7e1324,0x3dfab273,0xbf7ec46d,0xbdc8bd36,0xbf7c3b28,0xbe2f10a2,
0xbf45e403,0x3f226799,0xbf51c0c2,0x3f12c39a,0xbf6db293,0x3ebe1d4a,0xbf74484b,0x3e9920fe,0xbf7f4e6d,0x3d96a905,0xbf7fffb1,0xbb490fc6,
0xbf791298,0xbe6c9a7f,0xbf73ced9,0xbe9c1faf,0xbf54db31,0x3f0e39da,0xbf5f8327,0x3ef9a02d,0xbf76ba07,0x3e888e93,0xbf7b61fc,0x3e419b37,
0xbf7fb10f,0xbd48fb30,0xbf7de0b1,0xbe039502,0xbf6ed89e,0xbeb8442a,0xbf66becc,0xbeddbe79,0xbf61c598,0x3ef15aea,0xbf6afb8c,0x3ecb2aae,
0xbf7cbfc9,0x3e22abb6,0xbf7f3f54,0x3d9cecf9,0xbf7c3b28,0xbe2f10a2,0xbf77beb7,0xbe80f8c0,0xbf604621,0xbef6e0cb,0xbf554aa4,0xbf0d9281,
0xbf6c835e,0x3ec3ef15,0xbf740bdd,0x3e9aa086,0xbf7fb10f,0x3d48fb30,0xbf7fd397,0xbd16c32c,0xbf74fa0b,0xbe94a031,0xbf6db293,0xbebe1d4a,
0xbf4d9f02,0xbf187fc0,0xbf3fc767,0xbf299415,0xbf74fa0b,0x3e94a031,0xbf7a9c59,0x3e5101f1,0xbf7f84ab,0xbd7b2b74,0xbf7d1cdd,0xbe195be0,
0xbf6a09a7,0xbecf7bca,0xbf5fe4e9,0xbef840c8,0xbf373a23,0xbf32c8c9,0xbf269de3,0xbf425b89,0xbf7b14be,0x3e47c5c2,0xbf7e9bc9,0x3dd53db9,
0xbf7c3b28,0xbe2f10a2,0xbf772417,0xbe8586ce,0xbf5b941a,0xbf039c3d,0xbf4e8d90,0xbf173c07,0xbf1d7fd1,0xbf49d112,0xbf0a48ad,0xbf577026,
0xbf7ec46d,0x3dc8bd36,0xbf7fffb1,0x3b490fc6,0xbf75dec6,0xbe8e9a22,0xbf6dfcf2,0xbebca7af,0xbf49d112,0xbf1d7fd1,0xbf39f2ac,0xbf2ff3e6,
0xbf00e7e4,0xbf5d2d53,0xbed6a399,0xbf686b39,0x3f800000,0,0x3f800000,0,0x3f800000,0,0x3f800000,0,
0x3f800000,0,0x3f800000,0,0x3f800000,0,0x3f800000,0,0x3f7e9bc9,0x3dd53db9,0x3f7e868b,0x3ddb7d37,
0x3f7e4323,0x3dee3876,0x3f7e2b72,0x3df475c0,0x3f7de0b1,0x3e039502,0x3f7dc68c,0x3e06b26e,0x3f7d7474,0x3e1008b7,0x3f7d57de,0x3e1324ca,
0x3f7a7302,0x3e541501,0x3f7a1e84,0x3e5a3997,0x3f791298,0x3e6c9a7f,0x3f78b47b,0x3e72b651,0x3f778bc5,0x3e827dc0,0x3f772417,0x3e8586ce,
0x3f75dec6,0x3e8e9a22,0x3f756d97,0x3e919ddd,0x3f73913f,0x3e9d9e78,0x3f72d4eb,0x3ea21887,0x3f708066,0x3eaf713a,0x3f6faf1b,0x3eb3dca5,
0x3f6d1c1d,0x3ec1071e,0x3f6c3624,0x3ec5625c,0x3f696591,0x3ed25a09,0x3f686b39,0x3ed6a399,0x3f6a09a7,0x3ecf7bca,0x3f68bf3c,0x3ed53641,
0x3f64aa59,0x3ee63375,0x3f633c5a,0x3eebcbbb,0x3f5ebe05,0x3efc5d27,0x3f5d2d53,0x3f00e7e4,0x3f584853,0x3f08f59b,0x3f5695e5,0x3f0b9a6b,
0x3f5df6be,0x3eff17b2,0x3f5bfb34,0x3f02ef9f,0x3f55b993,0x3f0cead0,0x3f5389c7,0x3f102dd5,0x3f4cae79,0x3f19c200,0x3f4a4c87,0x3f1ce11f,
0x3f42de29,0x3f26050a,0x3f404c5c,0x3f28fd41,0x3f4f7a1f,0x3f15f6d9,0x3f4cae79,0x3f19c200,0x3f43e200,0x3f24d225,0x3f40d0da,0x3f286605,
0x3f373a23,0x3f32c8c9,0x3f33e7bc,0x3f36206c,0x3f299415,0x3f3fc767,0x3f26050a,0x3f42de29,0x3f3ebc1b,0x3f2ac082,0x3f3b0629,0x3f2ecef7,
0x3f2f61a5,0x3f3a7ca4,0x3f2b561b,0x3f3e35c5,0x3f1ebc12,0x3f48d8b3,0x3f1a6293,0x3f4c3578,0x3f0cead0,0x3f55b993,0x3f084b92,0x3f58b3a1,
0x3f2beb4a,0x3f3daef9,0x3f273656,0x3f41d870,0x3f187fc0,0x3f4d9f02,0x3f13682a,0x3f514d3d,0x3f039c3d,0x3f5b941a,0x3efc5d27,0x3f5ebe05,
0x3edae880,0x3f676bd8,0x3ecf7bca,0x3f6a09a7,0x3f173c07,0x3f4e8d90,0x3f11796b,0x3f52a649,0x3eff17b2,0x3f5df6be,0x3ef2bd43,0x3f61668a,
0x3ecc9b8b,0x3f6aab7b,0x3ebf926f,0x3f6d67a1,0x3e97a117,0x3f748422,0x3e8a11f7,0x3f76841b,0x3f00e7e4,0x3f5d2d53,0x3ef41f07,0x3f6106f2,
0x3ec9b953,0x3f6b4b0c,0x3ebb31a0,0x3f6e46be,0x3e8e9a22,0x3f75dec6,0x3e7ee6e1,0x3f77f110,0x3e22abb6,0x3f7cbfc9,0x3e039502,0x3f7de0b1,
0x3ed25a09,0x3f696591,0x3ec27b55,0x3f6cd007,0x3e919ddd,0x3f756d97,0x3e80f8c0,0x3f77beb7,0x3e1c76de,0x3f7cfe73,0x3df475c0,0x3f7e2b72,
0x3c96c9b6,0x3f7ff4e6,0xbc7b514b,0x3f7ff84a,0x3ea09ae5,0x3f731447,0x3e8e9a22,0x3f75dec6,0x3e2f10a2,0x3f7c3b28,0x3e09cf86,0x3f7dabcc,
0x3cc90ab0,0x3f7fec43,0xbc490e90,0x3f7ffb11,0xbdfab273,0x3f7e1324,0xbe22abb6,0x3f7cbfc9,0x3e5a3997,0x3f7a1e84,0x3e3228d4,0x3f7c187a,
0x3d621469,0x3f7f9c18,0x3c7b514b,0x3f7ff84a,0xbdd53db9,0x3f7e9bc9,0xbe1324ca,0x3f7d57de,0xbe8586ce,0x3f772417,0xbe9920fe,0x3f74484b,
0x3de1bc2e,0x3f7e70b0,0x3d8a200a,0x3f7f6ac7,0xbd7b2b74,0x3f7f84ab,0xbdd53db9,0x3f7e9bc9,0xbe6c9a7f,0x3f791298,0xbe8b9507,0x3f764d97,
0xbec9b953,0x3f6b4b0c,0xbeddbe79,0x3f66becc,0x3bc90f88,0x3f7ffec4,0xbd2351cb,0x3f7fcbe2,0xbe354098,0x3f7bf531,0xbe636c83,0x3f799b43,
0xbeb554ec,0x3f6f6830,0xbecb2aae,0x3f6afb8c,0xbf04f484,0x3f5ac450,0xbf0ee0db,0x3f546b3b,0xbdc8bd36,0x3f7ec46d,0xbe164083,0x3f7d3aac,
0xbe94a031,0x3f74fa0b,0xbeac7cd4,0x3f710908,0xbef15aea,0x3f61c598,0xbf039c3d,0x3f5b941a,0xbf226799,0x3f45e403,0xbf2beb4a,0x3f3daef9,
0xbe4dee60,0x3f7ac516,0xbe80f8c0,0x3f77beb7,0xbecc9b8b,0x3f6aab7b,0xbee4cbfe,0x3f650479,0xbf14b039,0x3f5064af,0xbf1f599f,0x3f485bca,
0xbf3ca003,0x3f2d1469,0xbf456439,0x3f2302d3,0xbe9aa086,0x3f740bdd,0xbeb554ec,0x3f6f6830,0xbf00e7e4,0x3f5d2d53,0xbf0cead0,0x3f55b993,
0xbf2e3bde,0x3f3b8f3b,0xbf385216,0x3f31a81d,0xbf531849,0x3f10d3cd,0xbf5ac450,0x3f04f484,0xbecc9b8b,0x3f6aab7b,0xbee79a5d,0x3f644fac,
0xbf19c200,0x3f4cae79,0xbf256bcb,0x3f436051,0xbf44e3f5,0x3f239da9,0xbf4e1689,0x3f17de12,0xbf655e0b,0x3ee363fa,0xbf6b99fb,0x3ec8477c,
0xbefc5d27,0x3f5ebe05,0xbf0b9a6b,0x3f5695e5,0xbf3085bb,0x3f396842,0xbf3b8f3b,0x3f2e3bde,0xbf584853,0x3f08f59b,0xbf604621,0x3ef6e0cb,
0xbf731447,0x3ea09ae5,0xbf778bc5,0x3e827dc0,0xbf14b039,0x3f5064af,0xbf21cbfb,0x3f466354,0xbf44e3f5,0x3f239da9,0xbf4f0417,0x3f16999f,
0xbf6816a8,0x3ed8106b,0xbf6e8ff8,0x3eb9bb1e,0xbf7bf531,0x3e354098,0xbf7e5a38,0x3de7fa9a,0xbf299415,0x3f3fc767,0xbf36206c,0x3f33e7bc,
0xbf5695e5,0x3f0b9a6b,0xbf5f8327,0x3ef9a02d,0xbf740bdd,0x3e9aa086,0xbf78b47b,0x3e72b651,0xbf7fd397,0x3d16c32c,0xbf7fe129,0xbcfb49ba,
0xbf3ca003,0x3f2d1469,0xbf485bca,0x3f1f599f,0xbf655e0b,0x3ee363fa,0xbf6cd007,0x3ec27b55,0xbf7bf531,0x3e354098,0xbf7e868b,0x3ddb7d37,
0xbf7e9bc9,0xbdd53db9,0xbf7c187a,0xbe3228d4,0xbf4d9f02,0x3f187fc0,0xbf584853,0x3f08f59b,0xbf710908,0x3eac7cd4,0xbf76ba07,0x3e888e93,
0xbf7fb10f,0x3d48fb30,0xbf7fec43,0xbcc90ab0,0xbf7853f8,0xbe78cfcc,0xbf731447,0xbea09ae5,0xbf5c61c7,0x3f0242b1,0xbf65b710,0x3ee1fb6a,
0xbf796e4e,0x3e667c66,0xbf7d1cdd,0x3e195be0,0xbf7f2f9d,0xbda3308c,0xbf7cdf6c,0xbe1f917b,0xbf6d1c1d,0xbec1071e,0xbf650479,0xbee4cbfe,
0xbf68bf3c,0x3ed53641,0xbf708066,0x3eaf713a,0xbf7e70b0,0x3de1bc2e,0xbf7fe129,0x3cfb49ba,0xbf7a7302,0xbe541501,0xbf756d97,0xbe919ddd,
0xbf5d2d53,0xbf00e7e4,0xbf5233c6,0xbf121eb0,0xbf7294f8,0x3ea395c5,0xbf788486,0x3e75c35a,0xbf7ffec4,0xbbc90f88,0xbf7efcc9,0xbdb5f8da,
0xbf718f57,0xbea986c4,0xbf69b7e4,0xbed0eb2a,0xbf48d8b3,0xbf1ebc12,0xbf3b0629,0xbf2ecef7,0xbf79c79d,0x3e605c13,0xbf7dabcc,0x3e09cf86,
0xbf7e1324,0xbdfab273,0xbf7a7302,0xbe541501,0xbf64aa59,0xbee63375,0xbf59f26a,0xbf064b82,0xbf3085bb,0xbf396842,0xbf1ff6cb,0xbf47de65,
0xbf7e4323,0x3dee3876,0xbf7fe705,0x3ce22a7a,0xbf78b47b,0xbe72b651,0xbf725470,0xbea5129f,0xbf53fac3,0xbf0f8784,0xbf466354,0xbf21cbfb,
0xbf14b039,0xbf5064af,0xbf019573,0xbf5cc7d1,0xbf7ffb11,0x3c490e90,0xbf7f2f9d,0xbda3308c,0xbf6ff573,0xbeb263ef,0xbf66becc,0xbeddbe79,
0xbf3fc767,0xbf299415,0xbf2f61a5,0xbf3a7ca4,0xbeebcbbb,0xbf633c5a,0xbec1071e,0xbf6d1c1d,0xbf7eea9d,0xbdbc3ac3,0xbf7b87b2,0xbe3e853e,
0xbf63f473,0xbee900b7,0xbf57dc7f,0xbf099f4e,0xbf286605,0xbf40d0da,0xbf1553b7,0xbf4fefa8,0xbea986c4,0xbf718f57,0xbe75c35a,0xbf788486,
0x3f800000,0,0x3f800000,0,0x3f800000,0,0x3f800000,0,0x3f800000,0,0x3f800000,0,
0x3f800000,0,0x3f800000,0,0x3f7d3aac,0x3e164083,0x3f7d1cdd,0x3e195be0,0x3f7cbfc9,0x3e22abb6,0x3f7c9f8a,0x3e25c58c,
0x3f7c3b28,0x3e2f10a2,0x3f7c187a,0x3e3228d4,0x3f7baccd,0x3e3b6ecf,0x3f7b87b2,0x3e3e853e,0x3f74fa0b,0x3e94a031,0x3f748422,0x3e97a117,
0x3f731447,0x3ea09ae5,0x3f7294f8,0x3ea395c5,0x3f710908,0x3eac7cd4,0x3f708066,0x3eaf713a,0x3f6ed89e,0x3eb8442a,0x3f6e46be,0x3ebb31a0,
0x3f676bd8,0x3edae880,0x3f666771,0x3edf28a9,0x3f633c5a,0x3eebcbbb,0x3f62241a,0x3eeff7fb,0x3f5ebe05,0x3efc5d27,0x3f5d924d,0x3f003a06,
0x3f59f26a,0x3f064b82,0x3f58b3a1,0x3f084b92,0x3f54db31,0x3f0e39da,0x3f531849,0x3f10d3cd,0x3f4d9f02,0x3f187fc0,0x3f4bbbf8,0x3f1b02c6,
0x3f45e403,0x3f226799,0x3f43e200,0x3f24d225,0x3f3daef9,0x3f2beb4a,0x3f3b8f3b,0x3f2e3bde,0x3f3daef9,0x3f2beb4a,0x3f3b0629,0x3f2ecef7,
0x3f32c8c9,0x3f373a23,0x3f2ff3e6,0x3f39f2ac,0x3f273656,0x3f41d870,0x3f24381a,0x3f446337,0x3f1b02c6,0x3f4bbbf8,0x3f17de12,0x3f4e1689,
0x3f226799,0x3f45e403,0x3f1ebc12,0x3f48d8b3,0x3f13682a,0x3f514d3d,0x3f0f8784,0x3f53fac3,0x3f039c3d,0x3f5b941a,0x3eff17b2,0x3f5df6be,
0x3ee63375,0x3f64aa59,0x3eddbe79,0x3f66becc,0x3f039c3d,0x3f5b941a,0x3efdbabb,0x3f5e5aa6,0x3ee0924f,0x3f660f88,0x3ed6a399,0x3f686b39,
0x3eb8442a,0x3f6ed89e,0x3eadf73c,0x3f70c501,0x3e8e9a22,0x3f75dec6,0x3e840270,0x3f77583a,0x3ec3ef15,0x3f6c835e,0x3eb8442a,0x3f6ed89e,
0x3e94a031,0x3f74fa0b,0x3e888e93,0x3f76ba07,0x3e47c5c2,0x3f7b14be,0x3e2f10a2,0x3f7c3b28,0x3dc8bd36,0x3f7ec46d,0x3d96a905,0x3f7f4e6d,
0x3e78cfcc,0x3f7853f8,0x3e5d4b1a,0x3f79f35e,0x3e09cf86,0x3f7dabcc,0x3ddb7d37,0x3f7e868b,0x3cc90ab0,0x3f7fec43,0xbb490fc6,0x3f7fffb1,
0xbdafb680,0x3f7f0e58,0xbde7fa9a,0x3f7e5a38,0x3dc8bd36,0x3f7ec46d,0x3d8a200a,0x3f7f6ac7,0xbcc90ab0,0x3f7fec43,0xbd621469,0x3f7f9c18,
0xbe164083,0x3f7d3aac,0xbe354098,0x3f7bf531,0xbe888e93,0x3f76ba07,0xbe97a117,0x3f748422,0xbd48fb30,0x3f7fb10f,0xbda973ba,0x3f7f1f49,
0xbe3b6ecf,0x3f7baccd,0xbe5d4b1a,0x3f79f35e,0xbea09ae5,0x3f731447,0xbeb0eacb,0x3f703b37,0xbee0924f,0x3f660f88,0xbeeff7fb,0x3f62241a,
0xbe47c5c2,0x3f7b14be,0xbe6c9a7f,0x3f791298,0xbeac7cd4,0x3f710908,0xbebe1d4a,0x3f6db293,0xbef15aea,0x3f61c598,0xbf00e7e4,0x3f5d2d53,
0xbf187fc0,0x3f4d9f02,0xbf1ff6cb,0x3f47de65,0xbeac7cd4,0x3f710908,0xbebf926f,0x3f6d67a1,0xbef6e0cb,0x3f604621,0xbf044889,0x3f5b2c79,
0xbf1d7fd1,0x3f49d112,0xbf256bcb,0x3f436051,0xbf3b8f3b,0x3f2e3bde,0xbf425b89,0x3f269de3,0xbef15aea,0x3f61c598,0xbf0242b1,0x3f5c61c7,
0xbf1d7fd1,0x3f49d112,0xbf26050a,0x3f42de29,0xbf3daef9,0x3f2beb4a,0xbf44e3f5,0x3f239da9,0xbf584853,0x3f08f59b,0xbf5df6be,0x3eff17b2,
0xbf187fc0,0x3f4d9f02,0xbf21cbfb,0x3f466354,0xbf3b8f3b,0x3f2e3bde,0xbf436051,0x3f256bcb,0xbf584853,0x3f08f59b,0xbf5e5aa6,0x3efdbabb,
0xbf6db293,0x3ebe1d4a,0xbf71d19f,0x3ea80b1f,0xbf3504f3,0x3f3504f3,0xbf3daef9,0x3f2beb4a,0xbf54db31,0x3f0e39da,0xbf5b941a,0x3f039c3d,
0xbf6c835e,0x3ec3ef15,0xbf710908,0x3eac7cd4,0xbf7b14be,0x3e47c5c2,0xbf7d3aac,0x3e164083,0xbf4d9f02,0x3f187fc0,0xbf554aa4,0x3f0d9281,
0xbf68bf3c,0x3ed53641,0xbf6dfcf2,0x3ebca7af,0xbf79c79d,0x3e605c13,0xbf7c5d3a,0x3e2bf804,0xbf7ffb11,0x3c490e90,0xbf7fcbe2,0xbd2351cb,
0xbf61c598,0x3ef15aea,0xbf6816a8,0x3ed8106b,0xbf76ba07,0x3e888e93,0xbf7a1e84,0x3e5a3997,0xbf7fb10f,0x3d48fb30,0xbf7ffec4,0xbbc90f88,
0xbf7c3b28,0xbe2f10a2,0xbf796e4e,0xbe667c66,0xbf710908,0x3eac7cd4,0xbf75a67b,0x3e901c2c,0xbf7e70b0,0x3de1bc2e,0xbf7fa6e3,0x3d55880e,
0xbf7e1324,0xbdfab273,0xbf7bd14d,0xbe3857ec,0xbf6ff573,0xbeb263ef,0xbf6a5ad9,0xbece0bea,0xbf7b14be,0x3e47c5c2,0xbf7dabcc,0x3e09cf86,
0xbf7fb10f,0xbd48fb30,0xbf7e70b0,0xbde1bc2e,0xbf74fa0b,0xbe94a031,0xbf6ff573,0xbeb263ef,0xbf5b941a,0xbf039c3d,0xbf531849,0xbf10d3cd,
0xbf7fb10f,0x3d48fb30,0xbf7ff84a,0xbc7b514b,0xbf7a7302,0xbe541501,0xbf76841b,0xbe8a11f7,0xbf64aa59,0xbee63375,0xbf5cc7d1,0xbf019573,
0xbf3fc767,0xbf299415,0xbf34768f,0xbf3592e7,0xbf7ec46d,0xbdc8bd36,0xbf7c7eb0,0xbe28defc,0xbf6ed89e,0xbeb8442a,0xbf6816a8,0xbed8106b,
0xbf4d9f02,0xbf187fc0,0xbf42de29,0xbf26050a,0xbf1d7fd1,0xbf49d112,0xbf0f8784,0xbf53fac3,0xbf7853f8,0xbe78cfcc,0xbf73530e,0xbe9f1cdf,
0xbf5d2d53,0xbf00e7e4,0xbf5389c7,0xbf102dd5,0xbf3085bb,0xbf396842,0xbf2302d3,0xbf456439,0xbeebcbbb,0xbf633c5a,0xbecb2aae,0xbf6afb8c,
0xbf6c835e,0xbec3ef15,0xbf64aa59,0xbee63375,0xbf45e403,0xbf226799,0xbf396842,0xbf3085bb,0xbf0e39da,0xbf54db31,0xbefc5d27,0xbf5ebe05,
0xbe94a031,0xbf74fa0b,0xbe605c13,0xbf79c79d,0xbf5b941a,0xbf039c3d,0xbf50d937,0xbf140c5f,0xbf299415,0xbf3fc767,0xbf1a6293,0xbf4c3578,
0xbecf7bca,0xbf6a09a7,0xbeab0201,0xbf714c7a,0xbde1bc2e,0xbf7e70b0,0xbd0a342f,0xbf7fdaaf,0xbf45e403,0xbf226799,0xbf385216,0xbf31a81d,
0xbf08f59b,0xbf584853,0xbeee9479,0xbf628210,0xbe78cfcc,0xbf7853f8,0xbe28defc,0xbf7c7eb0,0x3d96a905,0xbf7f4e6d,0x3e1c76de,0xbf7cfe73,
0xbf2beb4a,0xbf3daef9,0xbf1ba299,0xbf4b41fa,0xbec9b953,0xbf6b4b0c,0xbea21887,0xbf72d4eb,0xbd96a905,0xbf7f4e6d,0x3c16cb58,0xbf7ffd39,
0x3e827dc0,0xbf778bc5,0x3eab0201,0xbf714c7a,0xbf0e39da,0xbf54db31,0xbef6e0cb,0xbf604621,0xbe78cfcc,0xbf7853f8,0xbe22abb6,0xbf7cbfc9,
0x3dc8bd36,0xbf7ec46d,0x3e3b6ecf,0xbf7baccd,0x3edae880,0xbf676bd8,0x3f00e7e4,0xbf5d2d53,0xbedae880,0xbf676bd8,0xbeb0eacb,0xbf703b37,
0xbdafb680,0xbf7f0e58,0x3b490fc6,0xbf7fffb1,0x3e888e93,0xbf76ba07,0x3eb3dca5,0xbf6faf1b,0x3f15f6d9,0xbf4f7a1f,0x3f27ce61,0xbf4154e1,
0xbe94a031,0xbf74fa0b,0xbe4dee60,0xbf7ac516,0x3d96a905,0xbf7f4e6d,0x3e28defc,0xbf7c7eb0,0x3edae880,0xbf676bd8,0x3f0242b1,0xbf5c61c7,
0x3f396842,0xbf3085bb,0x3f48d8b3,0xbf1ebc12,0xbe164083,0xbf7d3aac,0xbd55880e,0xbf7fa6e3,0x3e6c9a7f,0xbf791298,0x3ea5129f,0xbf725470,
0x3f13682a,0xbf514d3d,0x3f269de3,0xbf425b89,0x3f5695e5,0xbf0b9a6b,0x3f62df7b,0xbeed3063,0x3f800000,0,0x3f800000,0,
0x3f800000,0,0x3f800000,0,0x3f800000,0,0x3f800000,0,0x3f800000,0,0x3f800000,0,
0x3f7cfe73,0x3e1c76de,0x3f7cdf6c,0x3e1f917b,0x3f7c7eb0,0x3e28defc,0x3f7c5d3a,0x3e2bf804,0x3f7bf531,0x3e354098,0x3f7bd14d,0x3e3857ec,
0x3f7b61fc,0x3e419b37,0x3f7b3bab,0x3e44b0b9,0x3f740bdd,0x3e9aa086,0x3f73913f,0x3e9d9e78,0x3f721352,0x3ea68f12,0x3f718f57,0x3ea986c4,
0x3f6ff573,0x3eb263ef,0x3f6f6830,0x3eb554ec,0x3f6db293,0x3ebe1d4a,0x3f6d1c1d,0x3ec1071e,0x3f655e0b,0x3ee363fa,0x3f644fac,0x3ee79a5d,
0x3f6106f2,0x3ef41f07,0x3f5fe4e9,0x3ef840c8,0x3f5c61c7,0x3f0242b1,0x3f5b2c79,0x3f044889,0x3f577026,0x3f0a48ad,0x3f5627fe,0x3f0c42c9,
0x3f514d3d,0x3f13682a,0x3f4f7a1f,0x3f15f6d9,0x3f49d112,0x3f1d7fd1,0x3f47de65,0x3f1ff6cb,0x3f41d870,0x3f273656,0x3f3fc767,0x3f299415,
0x3f396842,0x3f3085bb,0x3f373a23,0x3f32c8c9,0x3f385216,0x3f31a81d,0x3f3592e7,0x3f34768f,0x3f2d1469,0x3f3ca003,0x3f2a2a80,0x3f3f41fc,
0x3f212ff9,0x3f46e22a,0x3f1e1e22,0x3f495521,0x3f14b039,0x3f5064af,0x3f11796b,0x3f52a649,0x3f1b02c6,0x3f4bbbf8,0x3f173c07,0x3f4e8d90,
0x3f0b9a6b,0x3f5695e5,0x3f07a136,0x3f591e6a,0x3ef6e0cb,0x3f604621,0x3eee9479,0x3f628210,0x3ed53641,0x3f68bf3c,0x3ecc9b8b,0x3f6aab7b,
0x3ef41f07,0x3f6106f2,0x3eea6681,0x3f6398ac,0x3ecc9b8b,0x3f6aab7b,0x3ec27b55,0x3f6cd007,0x3ea395c5,0x3f7294f8,0x3e9920fe,0x3f74484b,
0x3e72b651,0x3f78b47b,0x3e5d4b1a,0x3f79f35e,0x3eac7cd4,0x3f710908,0x3ea09ae5,0x3f731447,0x3e78cfcc,0x3f7853f8,0x3e605c13,0x3f79c79d,
0x3e164083,0x3f7d3aac,0x3dfab273,0x3f7e1324,0x3d48fb30,0x3f7fb10f,0x3cc90ab0,0x3f7fec43,0x3e419b37,0x3f7b61fc,0x3e25c58c,0x3f7c9f8a,
0x3da3308c,0x3f7f2f9d,0x3d55880e,0x3f7fa6e3,0xbcfb49ba,0x3f7fe129,0xbd6ea038,0x3f7f90b1,0xbe1008b7,0x3f7d7474,0xbe2bf804,0x3f7c5d3a,
0x3d16c32c,0x3f7fd397,0x3bc90f88,0x3f7ffec4,0xbdafb680,0x3f7f0e58,0xbdee3876,0x3f7e4323,0xbe541501,0x3f7a7302,0xbe72b651,0x3f78b47b,
0xbea68f12,0x3f721352,0xbeb554ec,0x3f6f6830,0xbdee3876,0x3f7e4323,0xbe195be0,0x3f7d1cdd,0xbe7ee6e1,0x3f77f110,0xbe901c2c,0x3f75a67b,
0xbec1071e,0x3f6d1c1d,0xbed0eb2a,0x3f69b7e4,0xbeff17b2,0x3f5df6be,0xbf06f686,0x3f5988ad,0xbe888e93,0x3f76ba07,0xbe9aa086,0x3f740bdd,
0xbecf7bca,0x3f6a09a7,0xbee0924f,0x3f660f88,0xbf08f59b,0x3f584853,0xbf10d3cd,0x3f531849,0xbf273656,0x3f41d870,0xbf2e3bde,0x3f3b8f3b,
0xbed25a09,0x3f696591,0xbee4cbfe,0x3f650479,0xbf0cead0,0x3f55b993,0xbf1553b7,0x3f4fefa8,0xbf2d1469,0x3f3ca003,0xbf34768f,0x3f3592e7,
0xbf48d8b3,0x3f1ebc12,0xbf4f0417,0x3f16999f,0xbf0b9a6b,0x3f5695e5,0xbf14b039,0x3f5064af,0xbf2e3bde,0x3f3b8f3b,0xbf36206c,0x3f33e7bc,
0xbf4bbbf8,0x3f1b02c6,0xbf5233c6,0x3f121eb0,0xbf633c5a,0x3eebcbbb,0xbf6816a8,0x3ed8106b,0xbf2ac082,0x3f3ebc1b,0xbf33587a,0x3f36ad7f,
0xbf4ac77f,0x3f1c420c,0xbf51c0c2,0x3f12c39a,0xbf63f473,0x3ee900b7,0xbf6912ae,0x3ed3c867,0xbf756d97,0x3e919ddd,0xbf788486,0x3e75c35a,
0xbf45e403,0x3f226799,0xbf4d9f02,0x3f187fc0,0xbf61c598,0x3ef15aea,0xbf676bd8,0x3edae880,0xbf74fa0b,0x3e94a031,0xbf7853f8,0x3e78cfcc,
0xbf7ec46d,0x3dc8bd36,0xbf7fb10f,0x3d48fb30,0xbf5c61c7,0x3f0242b1,0xbf62df7b,0x3eed3063,0xbf7294f8,0x3ea395c5,0xbf76841b,0x3e8a11f7,
0xbf7e4323,0x3dee3876,0xbf7f7808,0x3d83db0a,0xbf7eea9d,0xbdbc3ac3,0xbf7d57de,0xbe1324ca,0xbf6db293,0x3ebe1d4a,0xbf7294f8,0x3ea395c5,
0xbf7cbfc9,0x3e22abb6,0xbf7e9bc9,0x3dd53db9,0xbf7f84ab,0xbd7b2b74,0xbf7e4323,0xbdee3876,0xbf75dec6,0xbe8e9a22,0xbf718f57,0xbea986c4,
0xbf796e4e,0x3e667c66,0xbf7c5d3a,0x3e2bf804,0xbf7ffec4,0xbbc90f88,0xbf7f7808,0xbd83db0a,0xbf78b47b,0xbe72b651,0xbf74bf62,0xbe9620d2,
0xbf63f473,0xbee900b7,0xbf5cc7d1,0xbf019573,0xbf7f4e6d,0x3d96a905,0xbf7ffb11,0x3c490e90,0xbf7c3b28,0xbe2f10a2,0xbf791298,0xbe6c9a7f,
0xbf6a09a7,0xbecf7bca,0xbf633c5a,0xbeebcbbb,0xbf49d112,0xbf1d7fd1,0xbf3fc767,0xbf299415,0xbf7f2f9d,0xbda3308c,0xbf7d57de,0xbe1324ca,
0xbf718f57,0xbea986c4,0xbf6b99fb,0xbec8477c,0xbf53fac3,0xbf0f8784,0xbf4a4c87,0xbf1ce11f,0xbf286605,0xbf40d0da,0xbf1ba299,0xbf4b41fa,
0xbf791298,0xbe6c9a7f,0xbf748422,0xbe97a117,0xbf604621,0xbef6e0cb,0xbf577026,0xbf0a48ad,0xbf373a23,0xbf32c8c9,0xbf2ac082,0xbf3ebc1b,
0xbf00e7e4,0xbf5d2d53,0xbee363fa,0xbf655e0b,0xbf6d1c1d,0xbec1071e,0xbf65b710,0xbee1fb6a,0xbf48d8b3,0xbf1ebc12,0xbf3d27b8,0xbf2c800f,
0xbf14b039,0xbf5064af,0xbf05a02c,0xbf5a5ba0,0xbea986c4,0xbf718f57,0xbe870ada,0xbf76ef5b,0xbf5b941a,0xbf039c3d,0xbf514d3d,0xbf13682a,
0xbf2beb4a,0xbf3daef9,0xbf1d7fd1,0xbf49d112,0xbedae880,0xbf676bd8,0xbeb8442a,0xbf6ed89e,0xbe164083,0xbf7d3aac,0xbd96a905,0xbf7f4e6d,
0xbf44e3f5,0xbf239da9,0xbf37c655,0xbf3238aa,0xbf0a48ad,0xbf577026,0xbef2bd43,0xbf61668a,0xbe8586ce,0xbf772417,0xbe3e853e,0xbf7b87b2,
0x3d2fe007,0xbf7fc38f,0x3df475c0,0xbf7e2b72,0xbf299415,0xbf3fc767,0xbf19c200,0xbf4cae79,0xbec9b953,0xbf6b4b0c,0xbea395c5,0xbf7294f8,
0xbdafb680,0xbf7f0e58,0xbbc90f88,0xbf7ffec4,0x3e6c9a7f,0xbf791298,0x3e9d9e78,0xbf73913f,0xbf0a48ad,0xbf577026,0xbeeff7fb,0xbf62241a,
0xbe72b651,0xbf78b47b,0xbe1f917b,0xbf7cdf6c,0x3dbc3ac3,0xbf7eea9d,0x3e3228d4,0xbf7c187a,0x3ed25a09,0xbf696591,0x3ef840c8,0xbf5fe4e9,
0xbecf7bca,0xbf6a09a7,0xbea68f12,0xbf721352,0xbd96a905,0xbf7f4e6d,0x3c490e90,0xbf7ffb11,0x3e888e93,0xbf76ba07,0x3eb263ef,0xbf6ff573,
0x3f13682a,0xbf514d3d,0x3f24d225,0xbf43e200,0xbe8586ce,0xbf772417,0xbe3228d4,0xbf7c187a,0x3dbc3ac3,0xbf7eea9d,0x3e3857ec,0xbf7bd14d,
0x3eddbe79,0xbf66becc,0x3f02ef9f,0xbf5bfb34,0x3f385216,0xbf31a81d,0x3f476085,0xbf209393,0xbde1bc2e,0xbf7e70b0,0xbc96c9b6,0xbf7ff4e6,
0x3e827dc0,0xbf778bc5,0x3eaf713a,0xbf708066,0x3f15f6d9,0xbf4f7a1f,0x3f286605,0xbf40d0da,0x3f5695e5,0xbf0b9a6b,0x3f628210,0xbeee9479,
0x3d2fe007,0xbf7fc38f,0x3e0cec4a,0xbf7d906e,0x3ed25a09,0xbf696591,0x3efdbabb,0xbf5e5aa6,0x3f385216,0xbf31a81d,0x3f485bca,0xbf1f599f,
0x3f6d1c1d,0xbec1071e,0x3f75341d,0xbe931f35,
};
__device__ __align__(1024) const uint32_t T_C64[4096] = {
0x3f803f80,0x3f803f80,0x3f803f80,0x3f803f80,0x3f803f80,0x3f803f80,0x3f803f80,0x3f803f80,0x3f803f80,0x3f803f80,0x3f803f80,0x3f803f80,
0x3f803f80,0x3f803f80,0x3f803f80,0x3f803f80,0x3f803f80,0x3f803f80,0x3f803f80,0x3f803f80,0x3f803f80,0x3f803f80,0x3f803f80,0x3f803f80,
0x3f803f80,0x3f803f80,0x3f803f80,0x3f803f80,0x3f803f80,0x3f803f80,0x3f803f80,0x3f803f80,0,0,0,0,
0,0,0,0,0,0,0,0,0,0,0,0,
0,0,0,0,0,0,0,0,0,0,0,0,
0,0,0,0,0x3f6d3f80,0xbec4248d,0xbf6dbf80,0x3ec4a554,0x3ec43f35,0xbf6dbf35,0xbec4bf35,0x3f6d3f35,
0x3f6d3f80,0xbec4248d,0xbf6dbf80,0x3ec4a554,0x3ec43f35,0xbf6dbf35,0xbec4bf35,0x3f6d3f35,0x3f6d3f80,0xbec4248d,0xbf6dbf80,0x3ec4a554,
0x3ec43f35,0xbf6dbf35,0xbec4bf35,0x3f6d3f35,0x3f6d3f80,0xbec4248d,0xbf6dbf80,0x3ec4a554,0x3ec43f35,0xbf6dbf35,0xbec4bf35,0x3f6d3f35,
0x3f6d3f35,0x3ec43f35,0xbf6dbf35,0xbec4bf35,0x3ec40000,0x3f6d3f80,0xbec4250d,0xbf6dbf80,0x3f6d3f35,0x3ec43f35,0xbf6dbf35,0xbec4bf35,
0x3ec40000,0x3f6d3f80,0xbec4250d,0xbf6dbf80,0x3f6d3f35,0x3ec43f35,0xbf6dbf35,0xbec4bf35,0x3ec40000,0x3f6d3f80,0xbec4250d,0xbf6dbf80,
0x3f6d3f35,0x3ec43f35,0xbf6dbf35,0xbec4bf35,0x3ec40000,0x3f6d3f80,0xbec4250d,0xbf6dbf80,0x3f353f80,0xbf35bf80,0x3f353f80,0xbf35bf80,
0xbf35248d,0x3f35a554,0xbf35248d,0x3f35a554,0x3f353f80,0xbf35bf80,0x3f353f80,0xbf35bf80,0xbf35248d,0x3f35a554,0xbf35248d,0x3f35a554,
0x3f353f80,0xbf35bf80,0x3f353f80,0xbf35bf80,0xbf35248d,0x3f35a554,0xbf35248d,0x3f35a554,0x3f353f80,0xbf35bf80,0x3f353f80,0xbf35bf80,
0xbf35248d,0x3f35a554,0xbf35248d,0x3f35a554,0x3f353f80,0xbf35bf80,0x3f353f80,0xbf35bf80,0x3f350000,0xbf35250d,0x3f350000,0xbf35250d,
0x3f353f80,0xbf35bf80,0x3f353f80,0xbf35bf80,0x3f350000,0xbf35250d,0x3f350000,0xbf35250d,0x3f353f80,0xbf35bf80,0x3f353f80,0xbf35bf80,
0x3f350000,0xbf35250d,0x3f350000,0xbf35250d,0x3f353f80,0xbf35bf80,0x3f353f80,0xbf35bf80,0x3f350000,0xbf35250d,0x3f350000,0xbf35250d,
0x3ec43f80,0x3f6da554,0xbec4bf80,0xbf6d248d,0xbf6dbf35,0xbec43f35,0x3f6d3f35,0x3ec4bf35,0x3ec43f80,0x3f6da554,0xbec4bf80,0xbf6d248d,
0xbf6dbf35,0xbec43f35,0x3f6d3f35,0x3ec4bf35,0x3ec43f80,0x3f6da554,0xbec4bf80,0xbf6d248d,0xbf6dbf35,0xbec43f35,0x3f6d3f35,0x3ec4bf35,
0x3ec43f80,0x3f6da554,0xbec4bf80,0xbf6d248d,0xbf6dbf35,0xbec43f35,0x3f6d3f35,0x3ec4bf35,0xbec43f35,0x3f6d3f35,0x3ec4bf35,0xbf6dbf35,
0x3f6d0000,0xbec4bf80,0xbf6d250d,0x3ec43f80,0xbec43f35,0x3f6d3f35,0x3ec4bf35,0xbf6dbf35,0x3f6d0000,0xbec4bf80,0xbf6d250d,0x3ec43f80,
0xbec43f35,0x3f6d3f35,0x3ec4bf35,0xbf6dbf35,0x3f6d0000,0xbec4bf80,0xbf6d250d,0x3ec43f80,0xbec43f35,0x3f6d3f35,0x3ec4bf35,0xbf6dbf35,
0x3f6d0000,0xbec4bf80,0xbf6d250d,0x3ec43f80,0x3f7f3f80,0x3f623f6d,0x3f223f35,0x3e953ec4,0x3f753f7b,0x3f463f55,0x3ef13f0e,0x3dc93e48,
0xbdc9248d,0xbef1bec4,0xbf46bf35,0xbf75bf6d,0xbe95be48,0xbf22bf0e,0xbf62bf55,0xbf7fbf7b,0xbf7fbf80,0xbf62bf6d,0xbf22bf35,0xbe95bec4,
0xbf75bf7b,0xbf46bf55,0xbef1bf0e,0xbdc9be48,0x3dc9a554,0x3ef13ec4,0x3f463f35,0x3f753f6d,0x3e953e48,0x3f223f0e,0x3f623f55,0x3f7f3f7b,
0x3e953e48,0x3f223f0e,0x3f623f55,0x3f7f3f7b,0x3dc90000,0x3ef13ec4,0x3f463f35,0x3f753f6d,0x3f753f7b,0x3f463f55,0x3ef13f0e,0x3dc93e48,
0x3f7f3f80,0x3f623f6d,0x3f223f35,0x3e953ec4,0xbe95be48,0xbf22bf0e,0xbf62bf55,0xbf7fbf7b,0xbdc9250d,0xbef1bec4,0xbf46bf35,0xbf75bf6d,
0xbf75bf7b,0xbf46bf55,0xbef1bf0e,0xbdc9be48,0xbf7fbf80,0xbf62bf6d,0xbf22bf35,0xbe95bec4,0xbef1248d,0xbf22bf6d,0x3f753f35,0xbdc93ec4,
0xbf7fbf55,0x3e95be48,0x3f463f7b,0xbf62bf0e,0x3f623f80,0xbf46bec4,0xbe95bf35,0x3f7f3f6d,0x3dc93f0e,0xbf75bf7b,0x3f223e48,0x3ef13f55,
0x3ef1a554,0x3f223f6d,0xbf75bf35,0x3dc9bec4,0x3f7f3f55,0xbe953e48,0xbf46bf7b,0x3f623f0e,0xbf62bf80,0x3f463ec4,0x3e953f35,0xbf7fbf6d,
0xbdc9bf0e,0x3f753f7b,0xbf22be48,0xbef1bf55,0x3dc93f0e,0xbf75bf7b,0x3f223e48,0x3ef13f55,0x3f623f80,0xbf46bec4,0xbe95bf35,0x3f7f3f6d,
0x3f7f3f55,0xbe953e48,0xbf46bf7b,0x3f623f0e,0x3ef10000,0x3f223f6d,0xbf75bf35,0x3dc9bec4,0xbdc9bf0e,0x3f753f7b,0xbf22be48,0xbef1bf55,
0xbf62bf80,0x3f463ec4,0x3e953f35,0xbf7fbf6d,0xbf7fbf55,0x3e95be48,0x3f463f7b,0xbf62bf0e,0xbef1250d,0xbf22bf6d,0x3f753f35,0xbdc93ec4,
0xbf22bf80,0x3e953f6d,0x3dc9bf35,0xbef13ec4,0x3f623e48,0xbf7fbf0e,0x3f753f55,0xbf46bf7b,0x3f46a554,0xbf75bec4,0x3f7f3f35,0xbf62bf6d,
0x3ef13f7b,0xbdc9bf55,0xbe953f0e,0x3f22be48,0x3f223f80,0xbe95bf6d,0xbdc93f35,0x3ef1bec4,0xbf62be48,0x3f7f3f0e,0xbf75bf55,0x3f463f7b,
0xbf46248d,0x3f753ec4,0xbf7fbf35,0x3f623f6d,0xbef1bf7b,0x3dc93f55,0x3e95bf0e,0xbf223e48,0xbef1bf7b,0x3dc93f55,0x3e95bf0e,0xbf223e48,
0xbf46250d,0x3f753ec4,0xbf7fbf35,0x3f623f6d,0x3f623e48,0xbf7fbf0e,0x3f753f55,0xbf46bf7b,0xbf22bf80,0x3e953f6d,0x3dc9bf35,0xbef13ec4,
0x3ef13f7b,0xbdc9bf55,0xbe953f0e,0x3f22be48,0x3f460000,0xbf75bec4,0x3f7f3f35,0xbf62bf6d,0xbf62be48,0x3f7f3f0e,0xbf75bf55,0x3f463f7b,
0x3f223f80,0xbe95bf6d,0xbdc93f35,0x3ef1bec4,0x3f75a554,0x3dc9bf6d,0xbf62bf35,0xbf463ec4,0xbf223f0e,0x3ef13f7b,0x3f7f3e48,0x3e95bf55,
0xbe95bf80,0xbf7fbec4,0xbef13f35,0x3f223f6d,0x3f463f55,0x3f62be48,0xbdc9bf7b,0xbf75bf0e,0xbf75248d,0xbdc93f6d,0x3f623f35,0x3f46bec4,
0x3f22bf0e,0xbef1bf7b,0xbf7fbe48,0xbe953f55,0x3e953f80,0x3f7f3ec4,0x3ef1bf35,0xbf22bf6d,0xbf46bf55,0xbf623e48,0x3dc93f7b,0x3f753f0e,
0x3f463f55,0x3f62be48,0xbdc9bf7b,0xbf75bf0e,0xbe95bf80,0xbf7fbec4,0xbef13f35,0x3f223f6d,0x3f22bf0e,0xbef1bf7b,0xbf7fbe48,0xbe953f55,
0xbf75250d,0xbdc93f6d,0x3f623f35,0x3f46bec4,0xbf46bf55,0xbf623e48,0x3dc93f7b,0x3f753f0e,0x3e953f80,0x3f7f3ec4,0x3ef1bf35,0xbf22bf6d,
0xbf223f0e,0x3ef13f7b,0x3f7f3e48,0x3e95bf55,0x3f750000,0x3dc9bf6d,0xbf62bf35,0xbf463ec4,0x3f7b3f80,0x3f0e3f35,0xbe48248d,0xbf55bf35,
0x3f553f6d,0x3e483ec4,0xbf0ebec4,0xbf7bbf6d,0xbf7bbf80,0xbf0ebf35,0x3e48a554,0x3f553f35,0xbf55bf6d,0xbe48bec4,0x3f0e3ec4,0x3f7b3f6d,
0x3f7b3f80,0x3f0e3f35,0xbe48248d,0xbf55bf35,0x3f553f6d,0x3e483ec4,0xbf0ebec4,0xbf7bbf6d,0xbf7bbf80,0xbf0ebf35,0x3e48a554,0x3f553f35,
0xbf55bf6d,0xbe48bec4,0x3f0e3ec4,0x3f7b3f6d,0x3f0e3ec4,0x3f7b3f6d,0x3f553f6d,0x3e483ec4,0x3e480000,0x3f553f35,0x3f7b3f80,0x3f0e3f35,
0xbf0ebec4,0xbf7bbf6d,0xbf55bf6d,0xbe48bec4,0xbe48250d,0xbf55bf35,0xbf7bbf80,0xbf0ebf35,0x3f0e3ec4,0x3f7b3f6d,0x3f553f6d,0x3e483ec4,
0x3e480000,0x3f553f35,0x3f7b3f80,0x3f0e3f35,0xbf0ebec4,0xbf7bbf6d,0xbf55bf6d,0xbe48bec4,0xbe48250d,0xbf55bf35,0xbf7bbf80,0xbf0ebf35,
0xbf55bf80,0x3f7b3f35,0xbf0e248d,0xbe48bf35,0x3e48bec4,0x3f0e3f6d,0xbf7bbf6d,0x3f553ec4,0x3f553f80,0xbf7bbf35,0x3f0ea554,0x3e483f35,
0xbe483ec4,0xbf0ebf6d,0x3f7b3f6d,0xbf55bec4,0xbf55bf80,0x3f7b3f35,0xbf0e248d,0xbe48bf35,0x3e48bec4,0x3f0e3f6d,0xbf7bbf6d,0x3f553ec4,
0x3f553f80,0xbf7bbf35,0x3f0ea554,0x3e483f35,0xbe483ec4,0xbf0ebf6d,0x3f7b3f6d,0xbf55bec4,0xbf7bbf6d,0x3f553ec4,0xbe483ec4,0xbf0ebf6d,
0xbf0e250d,0xbe48bf35,0x3f553f80,0xbf7bbf35,0x3f7b3f6d,0xbf55bec4,0x3e48bec4,0x3f0e3f6d,0x3f0e0000,0x3e483f35,0xbf55bf80,0x3f7b3f35,
0xbf7bbf6d,0x3f553ec4,0xbe483ec4,0xbf0ebf6d,0xbf0e250d,0xbe48bf35,0x3f553f80,0xbf7bbf35,0x3f7b3f6d,0xbf55bec4,0x3e48bec4,0x3f0e3f6d,
0x3f0e0000,0x3e483f35,0xbf55bf80,0x3f7b3f35,0x3f0e3f80,0x3e48bf35,0xbf55248d,0x3f7b3f35,0xbf7bbec4,0x3f553f6d,0xbe48bf6d,0xbf0e3ec4,
0xbf0ebf80,0xbe483f35,0x3f55a554,0xbf7bbf35,0x3f7b3ec4,0xbf55bf6d,0x3e483f6d,0x3f0ebec4,0x3f0e3f80,0x3e48bf35,0xbf55248d,0x3f7b3f35,
0xbf7bbec4,0x3f553f6d,0xbe48bf6d,0xbf0e3ec4,0xbf0ebf80,0xbe483f35,0x3f55a554,0xbf7bbf35,0x3f7b3ec4,0xbf55bf6d,0x3e483f6d,0x3f0ebec4,
0x3e483f6d,0x3f0ebec4,0xbf7bbec4,0x3f553f6d,0x3f550000,0xbf7bbf35,0x3f0e3f80,0x3e48bf35,0xbe48bf6d,0xbf0e3ec4,0x3f7b3ec4,0xbf55bf6d,
0xbf55250d,0x3f7b3f35,0xbf0ebf80,0xbe483f35,0x3e483f6d,0x3f0ebec4,0xbf7bbec4,0x3f553f6d,0x3f550000,0xbf7bbf35,0x3f0e3f80,0x3e48bf35,
0xbe48bf6d,0xbf0e3ec4,0x3f7b3ec4,0xbf55bf6d,0xbf55250d,0x3f7b3f35,0xbf0ebf80,0xbe483f35,0xbe48bf80,0xbf55bf35,0xbf7b248d,0xbf0e3f35,
0x3f0e3f6d,0x3f7b3ec4,0x3f55bec4,0x3e48bf6d,0x3e483f80,0x3f553f35,0x3f7ba554,0x3f0ebf35,0xbf0ebf6d,0xbf7bbec4,0xbf553ec4,0xbe483f6d,
0xbe48bf80,0xbf55bf35,0xbf7b248d,0xbf0e3f35,0x3f0e3f6d,0x3f7b3ec4,0x3f55bec4,0x3e48bf6d,0x3e483f80,0x3f553f35,0x3f7ba554,0x3f0ebf35,
0xbf0ebf6d,0xbf7bbec4,0xbf553ec4,0xbe483f6d,0x3f55bec4,0x3e48bf6d,0xbf0ebf6d,0xbf7bbec4,0xbf7b250d,0xbf0e3f35,0x3e483f80,0x3f553f35,
0xbf553ec4,0xbe483f6d,0x3f0e3f6d,0x3f7b3ec4,0x3f7b0000,0x3f0ebf35,0xbe48bf80,0xbf55bf35,0x3f55bec4,0x3e48bf6d,0xbf0ebf6d,0xbf7bbec4,
0xbf7b250d,0xbf0e3f35,0x3e483f80,0x3f553f35,0xbf553ec4,0xbe483f6d,0x3f0e3f6d,0x3f7b3ec4,0x3f7b0000,0x3f0ebf35,0xbe48bf80,0xbf55bf35,
0x3f753f80,0x3dc93ec4,0xbf62bf35,0xbf46bf6d,0x3f223f55,0xbef1be48,0xbf7fbf7b,0xbe95bf0e,0x3e95a554,0x3f7f3f6d,0x3ef13f35,0xbf22bec4,
0x3f463f0e,0x3f623f7b,0xbdc93e48,0xbf75bf55,0xbf75bf80,0xbdc9bec4,0x3f623f35,0x3f463f6d,0xbf22bf55,0x3ef13e48,0x3f7f3f7b,0x3e953f0e,
0xbe95248d,0xbf7fbf6d,0xbef1bf35,0x3f223ec4,0xbf46bf0e,0xbf62bf7b,0x3dc9be48,0x3f753f55,0x3f463f0e,0x3f623f7b,0xbdc93e48,0xbf75bf55,
0x3e950000,0x3f7f3f6d,0x3ef13f35,0xbf22bec4,0xbf22bf55,0x3ef13e48,0x3f7f3f7b,0x3e953f0e,0xbf75bf80,0xbdc9bec4,0x3f623f35,0x3f463f6d,
0xbf46bf0e,0xbf62bf7b,0x3dc9be48,0x3f753f55,0xbe95250d,0xbf7fbf6d,0xbef1bf35,0x3f223ec4,0x3f223f55,0xbef1be48,0xbf7fbf7b,0xbe95bf0e,
0x3f753f80,0x3dc93ec4,0xbf62bf35,0xbf46bf6d,0x3f22a554,0xbe953ec4,0xbdc9bf35,0x3ef13f6d,0x3f623f7b,0xbf7fbf55,0x3f753f0e,0xbf46be48,
0x3f463f80,0xbf75bf6d,0x3f7f3f35,0xbf62bec4,0xbef13e48,0x3dc9bf0e,0x3e953f55,0xbf22bf7b,0xbf22248d,0x3e95bec4,0x3dc93f35,0xbef1bf6d,
0xbf62bf7b,0x3f7f3f55,0xbf75bf0e,0x3f463e48,0xbf46bf80,0x3f753f6d,0xbf7fbf35,0x3f623ec4,0x3ef1be48,0xbdc93f0e,0xbe95bf55,0x3f223f7b,
0x3ef1be48,0xbdc93f0e,0xbe95bf55,0x3f223f7b,0xbf46bf80,0x3f753f6d,0xbf7fbf35,0x3f623ec4,0x3f623f7b,0xbf7fbf55,0x3f753f0e,0xbf46be48,
0x3f220000,0xbe953ec4,0xbdc9bf35,0x3ef13f6d,0xbef13e48,0x3dc9bf0e,0x3e953f55,0xbf22bf7b,0x3f463f80,0xbf75bf6d,0x3f7f3f35,0xbf62bec4,
0xbf62bf7b,0x3f7f3f55,0xbf75bf0e,0x3f463e48,0xbf22250d,0x3e95bec4,0x3dc93f35,0xbef1bf6d,0xbef1bf80,0xbf223ec4,0x3f753f35,0xbdc9bf6d,
0x3f7f3f0e,0xbe95bf7b,0xbf463e48,0x3f623f55,0xbf62248d,0x3f463f6d,0x3e95bf35,0xbf7fbec4,0x3dc9bf55,0xbf75be48,0x3f223f7b,0x3ef1bf0e,
0x3ef13f80,0x3f22bec4,0xbf75bf35,0x3dc93f6d,0xbf7fbf0e,0x3e953f7b,0x3f46be48,0xbf62bf55,0x3f62a554,0xbf46bf6d,0xbe953f35,0x3f7f3ec4,
0xbdc93f55,0x3f753e48,0xbf22bf7b,0xbef13f0e,0x3dc9bf55,0xbf75be48,0x3f223f7b,0x3ef1bf0e,0xbf62250d,0x3f463f6d,0x3e95bf35,0xbf7fbec4,
0xbf7fbf0e,0x3e953f7b,0x3f46be48,0xbf62bf55,0x3ef13f80,0x3f22bec4,0xbf75bf35,0x3dc93f6d,0xbdc93f55,0x3f753e48,0xbf22bf7b,0xbef13f0e,
0x3f620000,0xbf46bf6d,0xbe953f35,0x3f7f3ec4,0x3f7f3f0e,0xbe95bf7b,0xbf463e48,0x3f623f55,0xbef1bf80,0xbf223ec4,0x3f753f35,0xbdc9bf6d,
0xbf7f248d,0xbf623ec4,0xbf223f35,0xbe953f6d,0x3f75be48,0x3f46bf0e,0x3ef1bf55,0x3dc9bf7b,0xbdc9bf80,0xbef1bf6d,0xbf46bf35,0xbf75bec4,
0x3e953f7b,0x3f223f55,0x3f623f0e,0x3f7f3e48,0x3f7fa554,0x3f62bec4,0x3f22bf35,0x3e95bf6d,0xbf753e48,0xbf463f0e,0xbef13f55,0xbdc93f7b,
0x3dc93f80,0x3ef13f6d,0x3f463f35,0x3f753ec4,0xbe95bf7b,0xbf22bf55,0xbf62bf0e,0xbf7fbe48,0xbe95bf7b,0xbf22bf55,0xbf62bf0e,0xbf7fbe48,
0x3dc93f80,0x3ef13f6d,0x3f463f35,0x3f753ec4,0x3f75be48,0x3f46bf0e,0x3ef1bf55,0x3dc9bf7b,0xbf7f250d,0xbf623ec4,0xbf223f35,0xbe953f6d,
0x3e953f7b,0x3f223f55,0x3f623f0e,0x3f7f3e48,0xbdc9bf80,0xbef1bf6d,0xbf46bf35,0xbf75bec4,0xbf753e48,0xbf463f0e,0xbef13f55,0xbdc93f7b,
0x3f7f0000,0x3f62bec4,0x3f22bf35,0x3e95bf6d,0x248d3f80,0x248d3f80,0x248d3f80,0x248d3f80,0xa554bf80,0xa554bf80,0xa554bf80,0xa554bf80,
0x248d3f80,0x248d3f80,0x248d3f80,0x248d3f80,0xa554bf80,0xa554bf80,0xa554bf80,0xa554bf80,0x248d3f80,0x248d3f80,0x248d3f80,0x248d3f80,
0xa554bf80,0xa554bf80,0xa554bf80,0xa554bf80,0x248d3f80,0x248d3f80,0x248d3f80,0x248d3f80,0xa554bf80,0xa554bf80,0xa554bf80,0xa554bf80,
0xbf80250d,0xbf80250d,0xbf80250d,0xbf80250d,0x3f800000,0x3f800000,0x3f800000,0x3f800000,0xbf80250d,0xbf80250d,0xbf80250d,0xbf80250d,
0x3f800000,0x3f800000,0x3f800000,0x3f800000,0xbf80250d,0xbf80250d,0xbf80250d,0xbf80250d,0x3f800000,0x3f800000,0x3f800000,0x3f800000,
0xbf80250d,0xbf80250d,0xbf80250d,0xbf80250d,0x3f800000,0x3f800000,0x3f800000,0x3f800000,0xbec43f80,0xbf6d248d,0x3ec4bf80,0x3f6da554,
0x3f6dbf35,0x3ec43f35,0xbf6d3f35,0xbec4bf35,0xbec43f80,0xbf6d248d,0x3ec4bf80,0x3f6da554,0x3f6dbf35,0x3ec43f35,0xbf6d3f35,0xbec4bf35,
0xbec43f80,0xbf6d248d,0x3ec4bf80,0x3f6da554,0x3f6dbf35,0x3ec43f35,0xbf6d3f35,0xbec4bf35,0xbec43f80,0xbf6d248d,0x3ec4bf80,0x3f6da554,
0x3f6dbf35,0x3ec43f35,0xbf6d3f35,0xbec4bf35,0xbec4bf35,0x3f6dbf35,0x3ec43f35,0xbf6d3f35,0x3f6d0000,0xbec43f80,0xbf6d250d,0x3ec4bf80,
0xbec4bf35,0x3f6dbf35,0x3ec43f35,0xbf6d3f35,0x3f6d0000,0xbec43f80,0xbf6d250d,0x3ec4bf80,0xbec4bf35,0x3f6dbf35,0x3ec43f35,0xbf6d3f35,
0x3f6d0000,0xbec43f80,0xbf6d250d,0x3ec4bf80,0xbec4bf35,0x3f6dbf35,0x3ec43f35,0xbf6d3f35,0x3f6d0000,0xbec43f80,0xbf6d250d,0x3ec4bf80,
0xbf353f80,0x3f35bf80,0xbf353f80,0x3f35bf80,0x3f35a554,0xbf35248d,0x3f35a554,0xbf35248d,0xbf353f80,0x3f35bf80,0xbf353f80,0x3f35bf80,
0x3f35a554,0xbf35248d,0x3f35a554,0xbf35248d,0xbf353f80,0x3f35bf80,0xbf353f80,0x3f35bf80,0x3f35a554,0xbf35248d,0x3f35a554,0xbf35248d,
0xbf353f80,0x3f35bf80,0xbf353f80,0x3f35bf80,0x3f35a554,0xbf35248d,0x3f35a554,0xbf35248d,0x3f35bf80,0xbf353f80,0x3f35bf80,0xbf353f80,
0x3f350000,0xbf35250d,0x3f350000,0xbf35250d,0x3f35bf80,0xbf353f80,0x3f35bf80,0xbf353f80,0x3f350000,0xbf35250d,0x3f350000,0xbf35250d,
0x3f35bf80,0xbf353f80,0x3f35bf80,0xbf353f80,0x3f350000,0xbf35250d,0x3f350000,0xbf35250d,0x3f35bf80,0xbf353f80,0x3f35bf80,0xbf353f80,
0x3f350000,0xbf35250d,0x3f350000,0xbf35250d,0xbf6d3f80,0x3ec4a554,0x3f6dbf80,0xbec4248d,0xbec43f35,0x3f6dbf35,0x3ec4bf35,0xbf6d3f35,
0xbf6d3f80,0x3ec4a554,0x3f6dbf80,0xbec4248d,0xbec43f35,0x3f6dbf35,0x3ec4bf35,0xbf6d3f35,0xbf6d3f80,0x3ec4a554,0x3f6dbf80,0xbec4248d,
0xbec43f35,0x3f6dbf35,0x3ec4bf35,0xbf6d3f35,0xbf6d3f80,0x3ec4a554,0x3f6dbf80,0xbec4248d,0xbec43f35,0x3f6dbf35,0x3ec4bf35,0xbf6d3f35,
0x3f6dbf35,0x3ec4bf35,0xbf6d3f35,0xbec43f35,0x3ec40000,0x3f6dbf80,0xbec4250d,0xbf6d3f80,0x3f6dbf35,0x3ec4bf35,0xbf6d3f35,0xbec43f35,
0x3ec40000,0x3f6dbf80,0xbec4250d,0xbf6d3f80,0x3f6dbf35,0x3ec4bf35,0xbf6d3f35,0xbec43f35,0x3ec40000,0x3f6dbf80,0xbec4250d,0xbf6d3f80,
0x3f6dbf35,0x3ec4bf35,0xbf6d3f35,0xbec43f35,0x3ec40000,0x3f6dbf80,0xbec4250d,0xbf6d3f80,0xbdc93f80,0xbef13f6d,0xbf463f35,0xbf753ec4,
0x3e95bf7b,0x3f22bf55,0x3f62bf0e,0x3f7fbe48,0xbf7f248d,0xbf62bec4,0xbf22bf35,0xbe95bf6d,0x3f753e48,0x3f463f0e,0x3ef13f55,0x3dc93f7b,
0x3dc9bf80,0x3ef1bf6d,0x3f46bf35,0x3f75bec4,0xbe953f7b,0xbf223f55,0xbf623f0e,0xbf7f3e48,0x3f7fa554,0x3f623ec4,0x3f223f35,0x3e953f6d,
0xbf75be48,0xbf46bf0e,0xbef1bf55,0xbdc9bf7b,0xbf75be48,0xbf46bf0e,0xbef1bf55,0xbdc9bf7b,0x3f7f0000,0x3f623ec4,0x3f223f35,0x3e953f6d,
0x3e95bf7b,0x3f22bf55,0x3f62bf0e,0x3f7fbe48,0xbdc93f80,0xbef13f6d,0xbf463f35,0xbf753ec4,0x3f753e48,0x3f463f0e,0x3ef13f55,0x3dc93f7b,
0xbf7f250d,0xbf62bec4,0xbf22bf35,0xbe95bf6d,0xbe953f7b,0xbf223f55,0xbf623f0e,0xbf7f3e48,0x3dc9bf80,0x3ef1bf6d,0x3f46bf35,0x3f75bec4,
0xbf62248d,0x3f46bf6d,0x3e953f35,0xbf7f3ec4,0x3dc93f55,0xbf753e48,0x3f22bf7b,0x3ef13f0e,0xbef13f80,0xbf22bec4,0x3f75bf35,0xbdc93f6d,
0x3f7fbf0e,0xbe953f7b,0xbf46be48,0x3f62bf55,0x3f62a554,0xbf463f6d,0xbe95bf35,0x3f7fbec4,0xbdc9bf55,0x3f75be48,0xbf223f7b,0xbef1bf0e,
0x3ef1bf80,0x3f223ec4,0xbf753f35,0x3dc9bf6d,0xbf7f3f0e,0x3e95bf7b,0x3f463e48,0xbf623f55,0x3f7fbf0e,0xbe953f7b,0xbf46be48,0x3f62bf55,
0xbef13f80,0xbf22bec4,0x3f75bf35,0xbdc93f6d,0xbdc9bf55,0x3f75be48,0xbf223f7b,0xbef1bf0e,0x3f620000,0xbf463f6d,0xbe95bf35,0x3f7fbec4,
0xbf7f3f0e,0x3e95bf7b,0x3f463e48,0xbf623f55,0x3ef1bf80,0x3f223ec4,0xbf753f35,0x3dc9bf6d,0x3dc93f55,0xbf753e48,0x3f22bf7b,0x3ef13f0e,
0xbf62250d,0x3f46bf6d,0x3e953f35,0xbf7f3ec4,0x3f46bf80,0xbf753f6d,0x3f7fbf35,0xbf623ec4,0xbef1be48,0x3dc93f0e,0x3e95bf55,0xbf223f7b,
0x3f22a554,0xbe95bec4,0xbdc93f35,0x3ef1bf6d,0x3f62bf7b,0xbf7f3f55,0x3f75bf0e,0xbf463e48,0xbf463f80,0x3f75bf6d,0xbf7f3f35,0x3f62bec4,
0x3ef13e48,0xbdc9bf0e,0xbe953f55,0x3f22bf7b,0xbf22248d,0x3e953ec4,0x3dc9bf35,0xbef13f6d,0xbf623f7b,0x3f7fbf55,0xbf753f0e,0x3f46be48,
0xbf623f7b,0x3f7fbf55,0xbf753f0e,0x3f46be48,0xbf22250d,0x3e953ec4,0x3dc9bf35,0xbef13f6d,0xbef1be48,0x3dc93f0e,0x3e95bf55,0xbf223f7b,
0x3f46bf80,0xbf753f6d,0x3f7fbf35,0xbf623ec4,0x3f62bf7b,0xbf7f3f55,0x3f75bf0e,0xbf463e48,0x3f220000,0xbe95bec4,0xbdc93f35,0x3ef1bf6d,
0x3ef13e48,0xbdc9bf0e,0xbe953f55,0x3f22bf7b,0xbf463f80,0x3f75bf6d,0xbf7f3f35,0x3f62bec4,0x3e95a554,0x3f7fbf6d,0x3ef1bf35,0xbf223ec4,
0x3f46bf0e,0x3f62bf7b,0xbdc9be48,0xbf753f55,0x3f75bf80,0x3dc9bec4,0xbf623f35,0xbf463f6d,0x3f22bf55,0xbef13e48,0xbf7f3f7b,0xbe953f0e,
0xbe95248d,0xbf7f3f6d,0xbef13f35,0x3f22bec4,0xbf463f0e,0xbf623f7b,0x3dc93e48,0x3f75bf55,0xbf753f80,0xbdc93ec4,0x3f62bf35,0x3f46bf6d,
0xbf223f55,0x3ef1be48,0x3f7fbf7b,0x3e95bf0e,0x3f22bf55,0xbef13e48,0xbf7f3f7b,0xbe953f0e,0x3f75bf80,0x3dc9bec4,0xbf623f35,0xbf463f6d,
0xbf463f0e,0xbf623f7b,0x3dc93e48,0x3f75bf55,0xbe95250d,0xbf7f3f6d,0xbef13f35,0x3f22bec4,0xbf223f55,0x3ef1be48,0x3f7fbf7b,0x3e95bf0e,
0xbf753f80,0xbdc93ec4,0x3f62bf35,0x3f46bf6d,0x3f46bf0e,0x3f62bf7b,0xbdc9be48,0xbf753f55,0x3e950000,0x3f7fbf6d,0x3ef1bf35,0xbf223ec4,
0xbe483f80,0xbf553f35,0xbf7b248d,0xbf0ebf35,0x3f0ebf6d,0x3f7bbec4,0x3f553ec4,0x3e483f6d,0x3e48bf80,0x3f55bf35,0x3f7ba554,0x3f0e3f35,
0xbf0e3f6d,0xbf7b3ec4,0xbf55bec4,0xbe48bf6d,0xbe483f80,0xbf553f35,0xbf7b248d,0xbf0ebf35,0x3f0ebf6d,0x3f7bbec4,0x3f553ec4,0x3e483f6d,
0x3e48bf80,0x3f55bf35,0x3f7ba554,0x3f0e3f35,0xbf0e3f6d,0xbf7b3ec4,0xbf55bec4,0xbe48bf6d,0xbf55bec4,0xbe48bf6d,0x3f0ebf6d,0x3f7bbec4,
0x3f7b0000,0x3f0e3f35,0xbe483f80,0xbf553f35,0x3f553ec4,0x3e483f6d,0xbf0e3f6d,0xbf7b3ec4,0xbf7b250d,0xbf0ebf35,0x3e48bf80,0x3f55bf35,
0xbf55bec4,0xbe48bf6d,0x3f0ebf6d,0x3f7bbec4,0x3f7b0000,0x3f0e3f35,0xbe483f80,0xbf553f35,0x3f553ec4,0x3e483f6d,0xbf0e3f6d,0xbf7b3ec4,
0xbf7b250d,0xbf0ebf35,0x3e48bf80,0x3f55bf35,0x3f0ebf80,0x3e483f35,0xbf55248d,0x3f7bbf35,0xbf7b3ec4,0x3f55bf6d,0xbe483f6d,0xbf0ebec4,
0xbf0e3f80,0xbe48bf35,0x3f55a554,0xbf7b3f35,0x3f7bbec4,0xbf553f6d,0x3e48bf6d,0x3f0e3ec4,0x3f0ebf80,0x3e483f35,0xbf55248d,0x3f7bbf35,
0xbf7b3ec4,0x3f55bf6d,0xbe483f6d,0xbf0ebec4,0xbf0e3f80,0xbe48bf35,0x3f55a554,0xbf7b3f35,0x3f7bbec4,0xbf553f6d,0x3e48bf6d,0x3f0e3ec4,
0xbe483f6d,0xbf0ebec4,0x3f7bbec4,0xbf553f6d,0xbf55250d,0x3f7bbf35,0xbf0e3f80,0xbe48bf35,0x3e48bf6d,0x3f0e3ec4,0xbf7b3ec4,0x3f55bf6d,
0x3f550000,0xbf7b3f35,0x3f0ebf80,0x3e483f35,0xbe483f6d,0xbf0ebec4,0x3f7bbec4,0xbf553f6d,0xbf55250d,0x3f7bbf35,0xbf0e3f80,0xbe48bf35,
0x3e48bf6d,0x3f0e3ec4,0xbf7b3ec4,0x3f55bf6d,0x3f550000,0xbf7b3f35,0x3f0ebf80,0x3e483f35,0xbf553f80,0x3f7bbf35,0xbf0e248d,0xbe483f35,
0x3e483ec4,0x3f0ebf6d,0xbf7b3f6d,0x3f55bec4,0x3f55bf80,0xbf7b3f35,0x3f0ea554,0x3e48bf35,0xbe48bec4,0xbf0e3f6d,0x3f7bbf6d,0xbf553ec4,
0xbf553f80,0x3f7bbf35,0xbf0e248d,0xbe483f35,0x3e483ec4,0x3f0ebf6d,0xbf7b3f6d,0x3f55bec4,0x3f55bf80,0xbf7b3f35,0x3f0ea554,0x3e48bf35,
0xbe48bec4,0xbf0e3f6d,0x3f7bbf6d,0xbf553ec4,0x3f7bbf6d,0xbf553ec4,0x3e483ec4,0x3f0ebf6d,0x3f0e0000,0x3e48bf35,0xbf553f80,0x3f7bbf35,
0xbf7b3f6d,0x3f55bec4,0xbe48bec4,0xbf0e3f6d,0xbf0e250d,0xbe483f35,0x3f55bf80,0xbf7b3f35,0x3f7bbf6d,0xbf553ec4,0x3e483ec4,0x3f0ebf6d,
0x3f0e0000,0x3e48bf35,0xbf553f80,0x3f7bbf35,0xbf7b3f6d,0x3f55bec4,0xbe48bec4,0xbf0e3f6d,0xbf0e250d,0xbe483f35,0x3f55bf80,0xbf7b3f35,
0x3f7bbf80,0x3f0ebf35,0xbe48248d,0xbf553f35,0x3f55bf6d,0x3e48bec4,0xbf0e3ec4,0xbf7b3f6d,0xbf7b3f80,0xbf0e3f35,0x3e48a554,0x3f55bf35,
0xbf553f6d,0xbe483ec4,0x3f0ebec4,0x3f7bbf6d,0x3f7bbf80,0x3f0ebf35,0xbe48248d,0xbf553f35,0x3f55bf6d,0x3e48bec4,0xbf0e3ec4,0xbf7b3f6d,
0xbf7b3f80,0xbf0e3f35,0x3e48a554,0x3f55bf35,0xbf553f6d,0xbe483ec4,0x3f0ebec4,0x3f7bbf6d,0xbf0e3ec4,0xbf7b3f6d,0xbf553f6d,0xbe483ec4,
0xbe48250d,0xbf553f35,0xbf7b3f80,0xbf0e3f35,0x3f0ebec4,0x3f7bbf6d,0x3f55bf6d,0x3e48bec4,0x3e480000,0x3f55bf35,0x3f7bbf80,0x3f0ebf35,
0xbf0e3ec4,0xbf7b3f6d,0xbf553f6d,0xbe483ec4,0xbe48250d,0xbf553f35,0xbf7b3f80,0xbf0e3f35,0x3f0ebec4,0x3f7bbf6d,0x3f55bf6d,0x3e48bec4,
0x3e480000,0x3f55bf35,0x3f7bbf80,0x3f0ebf35,0xbe953f80,0xbf7f3ec4,0xbef1bf35,0x3f22bf6d,0x3f46bf55,0x3f623e48,0xbdc93f7b,0xbf753f0e,
0x3f75a554,0x3dc93f6d,0xbf623f35,0xbf46bec4,0xbf22bf0e,0x3ef1bf7b,0x3f7fbe48,0x3e953f55,0x3e95bf80,0x3f7fbec4,0x3ef13f35,0xbf223f6d,
0xbf463f55,0xbf62be48,0x3dc9bf7b,0x3f75bf0e,0xbf75248d,0xbdc9bf6d,0x3f62bf35,0x3f463ec4,0x3f223f0e,0xbef13f7b,0xbf7f3e48,0xbe95bf55,
0xbf22bf0e,0x3ef1bf7b,0x3f7fbe48,0x3e953f55,0x3f750000,0x3dc93f6d,0xbf623f35,0xbf46bec4,0xbf463f55,0xbf62be48,0x3dc9bf7b,0x3f75bf0e,
0x3e95bf80,0x3f7fbec4,0x3ef13f35,0xbf223f6d,0x3f223f0e,0xbef13f7b,0xbf7f3e48,0xbe95bf55,0xbf75250d,0xbdc9bf6d,0x3f62bf35,0x3f463ec4,
0x3f46bf55,0x3f623e48,0xbdc93f7b,0xbf753f0e,0xbe953f80,0xbf7f3ec4,0xbef1bf35,0x3f22bf6d,0x3f46a554,0xbf753ec4,0x3f7fbf35,0xbf623f6d,
0x3ef1bf7b,0xbdc93f55,0xbe95bf0e,0x3f223e48,0xbf223f80,0x3e95bf6d,0x3dc93f35,0xbef1bec4,0x3f62be48,0xbf7f3f0e,0x3f75bf55,0xbf463f7b,
0xbf46248d,0x3f75bec4,0xbf7f3f35,0x3f62bf6d,0xbef13f7b,0x3dc9bf55,0x3e953f0e,0xbf22be48,0x3f22bf80,0xbe953f6d,0xbdc9bf35,0x3ef13ec4,
0xbf623e48,0x3f7fbf0e,0xbf753f55,0x3f46bf7b,0xbf623e48,0x3f7fbf0e,0xbf753f55,0x3f46bf7b,0x3f22bf80,0xbe953f6d,0xbdc9bf35,0x3ef13ec4,
0x3ef1bf7b,0xbdc93f55,0xbe95bf0e,0x3f223e48,0x3f460000,0xbf753ec4,0x3f7fbf35,0xbf623f6d,0x3f62be48,0xbf7f3f0e,0x3f75bf55,0xbf463f7b,
0xbf223f80,0x3e95bf6d,0x3dc93f35,0xbef1bec4,0xbef13f7b,0x3dc9bf55,0x3e953f0e,0xbf22be48,0xbf46250d,0x3f75bec4,0xbf7f3f35,0x3f62bf6d,
0x3f62bf80,0xbf463ec4,0xbe953f35,0x3f7fbf6d,0x3dc9bf0e,0xbf753f7b,0x3f22be48,0x3ef1bf55,0xbef1248d,0xbf223f6d,0x3f75bf35,0xbdc9bec4,
0xbf7f3f55,0x3e953e48,0x3f46bf7b,0xbf623f0e,0xbf623f80,0x3f46bec4,0x3e95bf35,0xbf7f3f6d,0xbdc93f0e,0x3f75bf7b,0xbf223e48,0xbef13f55,
0x3ef1a554,0x3f22bf6d,0xbf753f35,0x3dc93ec4,0x3f7fbf55,0xbe95be48,0xbf463f7b,0x3f62bf0e,0xbf7f3f55,0x3e953e48,0x3f46bf7b,0xbf623f0e,
0xbef1250d,0xbf223f6d,0x3f75bf35,0xbdc9bec4,0xbdc93f0e,0x3f75bf7b,0xbf223e48,0xbef13f55,0xbf623f80,0x3f46bec4,0x3e95bf35,0xbf7f3f6d,
0x3f7fbf55,0xbe95be48,0xbf463f7b,0x3f62bf0e,0x3ef10000,0x3f22bf6d,0xbf753f35,0x3dc93ec4,0x3dc9bf0e,0xbf753f7b,0x3f22be48,0x3ef1bf55,
0x3f62bf80,0xbf463ec4,0xbe953f35,0x3f7fbf6d,0xbdc9248d,0xbef13ec4,0xbf463f35,0xbf753f6d,0xbe953e48,0xbf223f0e,0xbf623f55,0xbf7f3f7b,
0x3f7fbf80,0x3f62bf6d,0x3f22bf35,0x3e95bec4,0x3f75bf7b,0x3f46bf55,0x3ef1bf0e,0x3dc9be48,0x3dc9a554,0x3ef1bec4,0x3f46bf35,0x3f75bf6d,
0x3e95be48,0x3f22bf0e,0x3f62bf55,0x3f7fbf7b,0xbf7f3f80,0xbf623f6d,0xbf223f35,0xbe953ec4,0xbf753f7b,0xbf463f55,0xbef13f0e,0xbdc93e48,
0xbf753f7b,0xbf463f55,0xbef13f0e,0xbdc93e48,0xbf7f3f80,0xbf623f6d,0xbf223f35,0xbe953ec4,0xbe953e48,0xbf223f0e,0xbf623f55,0xbf7f3f7b,
0xbdc9250d,0xbef13ec4,0xbf463f35,0xbf753f6d,0x3f75bf7b,0x3f46bf55,0x3ef1bf0e,0x3dc9be48,0x3f7fbf80,0x3f62bf6d,0x3f22bf35,0x3e95bec4,
0x3e95be48,0x3f22bf0e,0x3f62bf55,0x3f7fbf7b,0x3dc90000,0x3ef1bec4,0x3f46bf35,0x3f75bf6d,0xbf803f80,0xbf803f80,0xbf803f80,0xbf803f80,
0xbf803f80,0xbf803f80,0xbf803f80,0xbf803f80,0xbf803f80,0xbf803f80,0xbf803f80,0xbf803f80,0xbf803f80,0xbf803f80,0xbf803f80,0xbf803f80,
0xbf803f80,0xbf803f80,0xbf803f80,0xbf803f80,0xbf803f80,0xbf803f80,0xbf803f80,0xbf803f80,0xbf803f80,0xbf803f80,0xbf803f80,0xbf803f80,
0xbf803f80,0xbf803f80,0xbf803f80,0xbf803f80,0x250d0000,0x250d0000,0x250d0000,0x250d0000,0x250d0000,0x250d0000,0x250d0000,0x250d0000,
0x250d0000,0x250d0000,0x250d0000,0x250d0000,0x250d0000,0x250d0000,0x250d0000,0x250d0000,0x250d0000,0x250d0000,0x250d0000,0x250d0000,
0x250d0000,0x250d0000,0x250d0000,0x250d0000,0x250d0000,0x250d0000,0x250d0000,0x250d0000,0x250d0000,0x250d0000,0x250d0000,0x250d0000,
0xbf6d3f80,0x3ec4248d,0x3f6dbf80,0xbec4a554,0xbec43f35,0x3f6dbf35,0x3ec4bf35,0xbf6d3f35,0xbf6d3f80,0x3ec4248d,0x3f6dbf80,0xbec4a554,
0xbec43f35,0x3f6dbf35,0x3ec4bf35,0xbf6d3f35,0xbf6d3f80,0x3ec4248d,0x3f6dbf80,0xbec4a554,0xbec43f35,0x3f6dbf35,0x3ec4bf35,0xbf6d3f35,
0xbf6d3f80,0x3ec4248d,0x3f6dbf80,0xbec4a554,0xbec43f35,0x3f6dbf35,0x3ec4bf35,0xbf6d3f35,0xbf6d3f35,0xbec43f35,0x3f6dbf35,0x3ec4bf35,
0xbec40000,0xbf6d3f80,0x3ec4250d,0x3f6dbf80,0xbf6d3f35,0xbec43f35,0x3f6dbf35,0x3ec4bf35,0xbec40000,0xbf6d3f80,0x3ec4250d,0x3f6dbf80,
0xbf6d3f35,0xbec43f35,0x3f6dbf35,0x3ec4bf35,0xbec40000,0xbf6d3f80,0x3ec4250d,0x3f6dbf80,0xbf6d3f35,0xbec43f35,0x3f6dbf35,0x3ec4bf35,
0xbec40000,0xbf6d3f80,0x3ec4250d,0x3f6dbf80,0xbf353f80,0x3f35bf80,0xbf353f80,0x3f35bf80,0x3f35248d,0xbf35a554,0x3f35248d,0xbf35a554,
0xbf353f80,0x3f35bf80,0xbf353f80,0x3f35bf80,0x3f35248d,0xbf35a554,0x3f35248d,0xbf35a554,0xbf353f80,0x3f35bf80,0xbf353f80,0x3f35bf80,
0x3f35248d,0xbf35a554,0x3f35248d,0xbf35a554,0xbf353f80,0x3f35bf80,0xbf353f80,0x3f35bf80,0x3f35248d,0xbf35a554,0x3f35248d,0xbf35a554,
0xbf353f80,0x3f35bf80,0xbf353f80,0x3f35bf80,0xbf350000,0x3f35250d,0xbf350000,0x3f35250d,0xbf353f80,0x3f35bf80,0xbf353f80,0x3f35bf80,
0xbf350000,0x3f35250d,0xbf350000,0x3f35250d,0xbf353f80,0x3f35bf80,0xbf353f80,0x3f35bf80,0xbf350000,0x3f35250d,0xbf350000,0x3f35250d,
0xbf353f80,0x3f35bf80,0xbf353f80,0x3f35bf80,0xbf350000,0x3f35250d,0xbf350000,0x3f35250d,0xbec43f80,0xbf6da554,0x3ec4bf80,0x3f6d248d,
0x3f6dbf35,0x3ec43f35,0xbf6d3f35,0xbec4bf35,0xbec43f80,0xbf6da554,0x3ec4bf80,0x3f6d248d,0x3f6dbf35,0x3ec43f35,0xbf6d3f35,0xbec4bf35,
0xbec43f80,0xbf6da554,0x3ec4bf80,0x3f6d248d,0x3f6dbf35,0x3ec43f35,0xbf6d3f35,0xbec4bf35,0xbec43f80,0xbf6da554,0x3ec4bf80,0x3f6d248d,
0x3f6dbf35,0x3ec43f35,0xbf6d3f35,0xbec4bf35,0x3ec43f35,0xbf6d3f35,0xbec4bf35,0x3f6dbf35,0xbf6d0000,0x3ec4bf80,0x3f6d250d,0xbec43f80,
0x3ec43f35,0xbf6d3f35,0xbec4bf35,0x3f6dbf35,0xbf6d0000,0x3ec4bf80,0x3f6d250d,0xbec43f80,0x3ec43f35,0xbf6d3f35,0xbec4bf35,0x3f6dbf35,
0xbf6d0000,0x3ec4bf80,0x3f6d250d,0xbec43f80,0x3ec43f35,0xbf6d3f35,0xbec4bf35,0x3f6dbf35,0xbf6d0000,0x3ec4bf80,0x3f6d250d,0xbec43f80,
0xbf7f3f80,0xbf623f6d,0xbf223f35,0xbe953ec4,0xbf753f7b,0xbf463f55,0xbef13f0e,0xbdc93e48,0x3dc9248d,0x3ef1bec4,0x3f46bf35,0x3f75bf6d,
0x3e95be48,0x3f22bf0e,0x3f62bf55,0x3f7fbf7b,0x3f7fbf80,0x3f62bf6d,0x3f22bf35,0x3e95bec4,0x3f75bf7b,0x3f46bf55,0x3ef1bf0e,0x3dc9be48,
0xbdc9a554,0xbef13ec4,0xbf463f35,0xbf753f6d,0xbe953e48,0xbf223f0e,0xbf623f55,0xbf7f3f7b,0xbe953e48,0xbf223f0e,0xbf623f55,0xbf7f3f7b,
0xbdc90000,0xbef13ec4,0xbf463f35,0xbf753f6d,0xbf753f7b,0xbf463f55,0xbef13f0e,0xbdc93e48,0xbf7f3f80,0xbf623f6d,0xbf223f35,0xbe953ec4,
0x3e95be48,0x3f22bf0e,0x3f62bf55,0x3f7fbf7b,0x3dc9250d,0x3ef1bec4,0x3f46bf35,0x3f75bf6d,0x3f75bf7b,0x3f46bf55,0x3ef1bf0e,0x3dc9be48,
0x3f7fbf80,0x3f62bf6d,0x3f22bf35,0x3e95bec4,0x3ef1248d,0x3f22bf6d,0xbf753f35,0x3dc93ec4,0x3f7fbf55,0xbe95be48,0xbf463f7b,0x3f62bf0e,
0xbf623f80,0x3f46bec4,0x3e95bf35,0xbf7f3f6d,0xbdc93f0e,0x3f75bf7b,0xbf223e48,0xbef13f55,0xbef1a554,0xbf223f6d,0x3f75bf35,0xbdc9bec4,
0xbf7f3f55,0x3e953e48,0x3f46bf7b,0xbf623f0e,0x3f62bf80,0xbf463ec4,0xbe953f35,0x3f7fbf6d,0x3dc9bf0e,0xbf753f7b,0x3f22be48,0x3ef1bf55,
0xbdc93f0e,0x3f75bf7b,0xbf223e48,0xbef13f55,0xbf623f80,0x3f46bec4,0x3e95bf35,0xbf7f3f6d,0xbf7f3f55,0x3e953e48,0x3f46bf7b,0xbf623f0e,
0xbef10000,0xbf223f6d,0x3f75bf35,0xbdc9bec4,0x3dc9bf0e,0xbf753f7b,0x3f22be48,0x3ef1bf55,0x3f62bf80,0xbf463ec4,0xbe953f35,0x3f7fbf6d,
0x3f7fbf55,0xbe95be48,0xbf463f7b,0x3f62bf0e,0x3ef1250d,0x3f22bf6d,0xbf753f35,0x3dc93ec4,0x3f22bf80,0xbe953f6d,0xbdc9bf35,0x3ef13ec4,
0xbf623e48,0x3f7fbf0e,0xbf753f55,0x3f46bf7b,0xbf46a554,0x3f75bec4,0xbf7f3f35,0x3f62bf6d,0xbef13f7b,0x3dc9bf55,0x3e953f0e,0xbf22be48,
0xbf223f80,0x3e95bf6d,0x3dc93f35,0xbef1bec4,0x3f62be48,0xbf7f3f0e,0x3f75bf55,0xbf463f7b,0x3f46248d,0xbf753ec4,0x3f7fbf35,0xbf623f6d,
0x3ef1bf7b,0xbdc93f55,0xbe95bf0e,0x3f223e48,0x3ef1bf7b,0xbdc93f55,0xbe95bf0e,0x3f223e48,0x3f46250d,0xbf753ec4,0x3f7fbf35,0xbf623f6d,
0xbf623e48,0x3f7fbf0e,0xbf753f55,0x3f46bf7b,0x3f22bf80,0xbe953f6d,0xbdc9bf35,0x3ef13ec4,0xbef13f7b,0x3dc9bf55,0x3e953f0e,0xbf22be48,
0xbf460000,0x3f75bec4,0xbf7f3f35,0x3f62bf6d,0x3f62be48,0xbf7f3f0e,0x3f75bf55,0xbf463f7b,0xbf223f80,0x3e95bf6d,0x3dc93f35,0xbef1bec4,
0xbf75a554,0xbdc9bf6d,0x3f62bf35,0x3f463ec4,0x3f223f0e,0xbef13f7b,0xbf7f3e48,0xbe95bf55,0x3e95bf80,0x3f7fbec4,0x3ef13f35,0xbf223f6d,
0xbf463f55,0xbf62be48,0x3dc9bf7b,0x3f75bf0e,0x3f75248d,0x3dc93f6d,0xbf623f35,0xbf46bec4,0xbf22bf0e,0x3ef1bf7b,0x3f7fbe48,0x3e953f55,
0xbe953f80,0xbf7f3ec4,0xbef1bf35,0x3f22bf6d,0x3f46bf55,0x3f623e48,0xbdc93f7b,0xbf753f0e,0xbf463f55,0xbf62be48,0x3dc9bf7b,0x3f75bf0e,
0x3e95bf80,0x3f7fbec4,0x3ef13f35,0xbf223f6d,0xbf22bf0e,0x3ef1bf7b,0x3f7fbe48,0x3e953f55,0x3f75250d,0x3dc93f6d,0xbf623f35,0xbf46bec4,
0x3f46bf55,0x3f623e48,0xbdc93f7b,0xbf753f0e,0xbe953f80,0xbf7f3ec4,0xbef1bf35,0x3f22bf6d,0x3f223f0e,0xbef13f7b,0xbf7f3e48,0xbe95bf55,
0xbf750000,0xbdc9bf6d,0x3f62bf35,0x3f463ec4,0xbf7b3f80,0xbf0e3f35,0x3e48248d,0x3f55bf35,0xbf553f6d,0xbe483ec4,0x3f0ebec4,0x3f7bbf6d,
0x3f7bbf80,0x3f0ebf35,0xbe48a554,0xbf553f35,0x3f55bf6d,0x3e48bec4,0xbf0e3ec4,0xbf7b3f6d,0xbf7b3f80,0xbf0e3f35,0x3e48248d,0x3f55bf35,
0xbf553f6d,0xbe483ec4,0x3f0ebec4,0x3f7bbf6d,0x3f7bbf80,0x3f0ebf35,0xbe48a554,0xbf553f35,0x3f55bf6d,0x3e48bec4,0xbf0e3ec4,0xbf7b3f6d,
0xbf0e3ec4,0xbf7b3f6d,0xbf553f6d,0xbe483ec4,0xbe480000,0xbf553f35,0xbf7b3f80,0xbf0e3f35,0x3f0ebec4,0x3f7bbf6d,0x3f55bf6d,0x3e48bec4,
0x3e48250d,0x3f55bf35,0x3f7bbf80,0x3f0ebf35,0xbf0e3ec4,0xbf7b3f6d,0xbf553f6d,0xbe483ec4,0xbe480000,0xbf553f35,0xbf7b3f80,0xbf0e3f35,
0x3f0ebec4,0x3f7bbf6d,0x3f55bf6d,0x3e48bec4,0x3e48250d,0x3f55bf35,0x3f7bbf80,0x3f0ebf35,0x3f55bf80,0xbf7b3f35,0x3f0e248d,0x3e48bf35,
0xbe48bec4,0xbf0e3f6d,0x3f7bbf6d,0xbf553ec4,0xbf553f80,0x3f7bbf35,0xbf0ea554,0xbe483f35,0x3e483ec4,0x3f0ebf6d,0xbf7b3f6d,0x3f55bec4,
0x3f55bf80,0xbf7b3f35,0x3f0e248d,0x3e48bf35,0xbe48bec4,0xbf0e3f6d,0x3f7bbf6d,0xbf553ec4,0xbf553f80,0x3f7bbf35,0xbf0ea554,0xbe483f35,
0x3e483ec4,0x3f0ebf6d,0xbf7b3f6d,0x3f55bec4,0x3f7bbf6d,0xbf553ec4,0x3e483ec4,0x3f0ebf6d,0x3f0e250d,0x3e48bf35,0xbf553f80,0x3f7bbf35,
0xbf7b3f6d,0x3f55bec4,0xbe48bec4,0xbf0e3f6d,0xbf0e0000,0xbe483f35,0x3f55bf80,0xbf7b3f35,0x3f7bbf6d,0xbf553ec4,0x3e483ec4,0x3f0ebf6d,
0x3f0e250d,0x3e48bf35,0xbf553f80,0x3f7bbf35,0xbf7b3f6d,0x3f55bec4,0xbe48bec4,0xbf0e3f6d,0xbf0e0000,0xbe483f35,0x3f55bf80,0xbf7b3f35,
0xbf0e3f80,0xbe48bf35,0x3f55248d,0xbf7b3f35,0x3f7bbec4,0xbf553f6d,0x3e48bf6d,0x3f0e3ec4,0x3f0ebf80,0x3e483f35,0xbf55a554,0x3f7bbf35,
0xbf7b3ec4,0x3f55bf6d,0xbe483f6d,0xbf0ebec4,0xbf0e3f80,0xbe48bf35,0x3f55248d,0xbf7b3f35,0x3f7bbec4,0xbf553f6d,0x3e48bf6d,0x3f0e3ec4,
0x3f0ebf80,0x3e483f35,0xbf55a554,0x3f7bbf35,0xbf7b3ec4,0x3f55bf6d,0xbe483f6d,0xbf0ebec4,0xbe483f6d,0xbf0ebec4,0x3f7bbec4,0xbf553f6d,
0xbf550000,0x3f7bbf35,0xbf0e3f80,0xbe48bf35,0x3e48bf6d,0x3f0e3ec4,0xbf7b3ec4,0x3f55bf6d,0x3f55250d,0xbf7b3f35,0x3f0ebf80,0x3e483f35,
0xbe483f6d,0xbf0ebec4,0x3f7bbec4,0xbf553f6d,0xbf550000,0x3f7bbf35,0xbf0e3f80,0xbe48bf35,0x3e48bf6d,0x3f0e3ec4,0xbf7b3ec4,0x3f55bf6d,
0x3f55250d,0xbf7b3f35,0x3f0ebf80,0x3e483f35,0x3e48bf80,0x3f55bf35,0x3f7b248d,0x3f0e3f35,0xbf0e3f6d,0xbf7b3ec4,0xbf55bec4,0xbe48bf6d,
0xbe483f80,0xbf553f35,0xbf7ba554,0xbf0ebf35,0x3f0ebf6d,0x3f7bbec4,0x3f553ec4,0x3e483f6d,0x3e48bf80,0x3f55bf35,0x3f7b248d,0x3f0e3f35,
0xbf0e3f6d,0xbf7b3ec4,0xbf55bec4,0xbe48bf6d,0xbe483f80,0xbf553f35,0xbf7ba554,0xbf0ebf35,0x3f0ebf6d,0x3f7bbec4,0x3f553ec4,0x3e483f6d,
0xbf55bec4,0xbe48bf6d,0x3f0ebf6d,0x3f7bbec4,0x3f7b250d,0x3f0e3f35,0xbe483f80,0xbf553f35,0x3f553ec4,0x3e483f6d,0xbf0e3f6d,0xbf7b3ec4,
0xbf7b0000,0xbf0ebf35,0x3e48bf80,0x3f55bf35,0xbf55bec4,0xbe48bf6d,0x3f0ebf6d,0x3f7bbec4,0x3f7b250d,0x3f0e3f35,0xbe483f80,0xbf553f35,
0x3f553ec4,0x3e483f6d,0xbf0e3f6d,0xbf7b3ec4,0xbf7b0000,0xbf0ebf35,0x3e48bf80,0x3f55bf35,0xbf753f80,0xbdc93ec4,0x3f62bf35,0x3f46bf6d,
0xbf223f55,0x3ef1be48,0x3f7fbf7b,0x3e95bf0e,0xbe95a554,0xbf7f3f6d,0xbef13f35,0x3f22bec4,0xbf463f0e,0xbf623f7b,0x3dc93e48,0x3f75bf55,
0x3f75bf80,0x3dc9bec4,0xbf623f35,0xbf463f6d,0x3f22bf55,0xbef13e48,0xbf7f3f7b,0xbe953f0e,0x3e95248d,0x3f7fbf6d,0x3ef1bf35,0xbf223ec4,
0x3f46bf0e,0x3f62bf7b,0xbdc9be48,0xbf753f55,0xbf463f0e,0xbf623f7b,0x3dc93e48,0x3f75bf55,0xbe950000,0xbf7f3f6d,0xbef13f35,0x3f22bec4,
0x3f22bf55,0xbef13e48,0xbf7f3f7b,0xbe953f0e,0x3f75bf80,0x3dc9bec4,0xbf623f35,0xbf463f6d,0x3f46bf0e,0x3f62bf7b,0xbdc9be48,0xbf753f55,
0x3e95250d,0x3f7fbf6d,0x3ef1bf35,0xbf223ec4,0xbf223f55,0x3ef1be48,0x3f7fbf7b,0x3e95bf0e,0xbf753f80,0xbdc93ec4,0x3f62bf35,0x3f46bf6d,
0xbf22a554,0x3e953ec4,0x3dc9bf35,0xbef13f6d,0xbf623f7b,0x3f7fbf55,0xbf753f0e,0x3f46be48,0xbf463f80,0x3f75bf6d,0xbf7f3f35,0x3f62bec4,
0x3ef13e48,0xbdc9bf0e,0xbe953f55,0x3f22bf7b,0x3f22248d,0xbe95bec4,0xbdc93f35,0x3ef1bf6d,0x3f62bf7b,0xbf7f3f55,0x3f75bf0e,0xbf463e48,
0x3f46bf80,0xbf753f6d,0x3f7fbf35,0xbf623ec4,0xbef1be48,0x3dc93f0e,0x3e95bf55,0xbf223f7b,0xbef1be48,0x3dc93f0e,0x3e95bf55,0xbf223f7b,
0x3f46bf80,0xbf753f6d,0x3f7fbf35,0xbf623ec4,0xbf623f7b,0x3f7fbf55,0xbf753f0e,0x3f46be48,0xbf220000,0x3e953ec4,0x3dc9bf35,0xbef13f6d,
0x3ef13e48,0xbdc9bf0e,0xbe953f55,0x3f22bf7b,0xbf463f80,0x3f75bf6d,0xbf7f3f35,0x3f62bec4,0x3f62bf7b,0xbf7f3f55,0x3f75bf0e,0xbf463e48,
0x3f22250d,0xbe95bec4,0xbdc93f35,0x3ef1bf6d,0x3ef1bf80,0x3f223ec4,0xbf753f35,0x3dc9bf6d,0xbf7f3f0e,0x3e95bf7b,0x3f463e48,0xbf623f55,
0x3f62248d,0xbf463f6d,0xbe95bf35,0x3f7fbec4,0xbdc9bf55,0x3f75be48,0xbf223f7b,0xbef1bf0e,0xbef13f80,0xbf22bec4,0x3f75bf35,0xbdc93f6d,
0x3f7fbf0e,0xbe953f7b,0xbf46be48,0x3f62bf55,0xbf62a554,0x3f46bf6d,0x3e953f35,0xbf7f3ec4,0x3dc93f55,0xbf753e48,0x3f22bf7b,0x3ef13f0e,
0xbdc9bf55,0x3f75be48,0xbf223f7b,0xbef1bf0e,0x3f62250d,0xbf463f6d,0xbe95bf35,0x3f7fbec4,0x3f7fbf0e,0xbe953f7b,0xbf46be48,0x3f62bf55,
0xbef13f80,0xbf22bec4,0x3f75bf35,0xbdc93f6d,0x3dc93f55,0xbf753e48,0x3f22bf7b,0x3ef13f0e,0xbf620000,0x3f46bf6d,0x3e953f35,0xbf7f3ec4,
0xbf7f3f0e,0x3e95bf7b,0x3f463e48,0xbf623f55,0x3ef1bf80,0x3f223ec4,0xbf753f35,0x3dc9bf6d,0x3f7f248d,0x3f623ec4,0x3f223f35,0x3e953f6d,
0xbf75be48,0xbf46bf0e,0xbef1bf55,0xbdc9bf7b,0x3dc9bf80,0x3ef1bf6d,0x3f46bf35,0x3f75bec4,0xbe953f7b,0xbf223f55,0xbf623f0e,0xbf7f3e48,
0xbf7fa554,0xbf62bec4,0xbf22bf35,0xbe95bf6d,0x3f753e48,0x3f463f0e,0x3ef13f55,0x3dc93f7b,0xbdc93f80,0xbef13f6d,0xbf463f35,0xbf753ec4,
0x3e95bf7b,0x3f22bf55,0x3f62bf0e,0x3f7fbe48,0x3e95bf7b,0x3f22bf55,0x3f62bf0e,0x3f7fbe48,0xbdc93f80,0xbef13f6d,0xbf463f35,0xbf753ec4,
0xbf75be48,0xbf46bf0e,0xbef1bf55,0xbdc9bf7b,0x3f7f250d,0x3f623ec4,0x3f223f35,0x3e953f6d,0xbe953f7b,0xbf223f55,0xbf623f0e,0xbf7f3e48,
0x3dc9bf80,0x3ef1bf6d,0x3f46bf35,0x3f75bec4,0x3f753e48,0x3f463f0e,0x3ef13f55,0x3dc93f7b,0xbf7f0000,0xbf62bec4,0xbf22bf35,0xbe95bf6d,
0xa5543f80,0xa5543f80,0xa5543f80,0xa5543f80,0x248dbf80,0x248dbf80,0x248dbf80,0x248dbf80,0xa5543f80,0xa5543f80,0xa5543f80,0xa5543f80,
0x248dbf80,0x248dbf80,0x248dbf80,0x248dbf80,0xa5543f80,0xa5543f80,0xa5543f80,0xa5543f80,0x248dbf80,0x248dbf80,0x248dbf80,0x248dbf80,
0xa5543f80,0xa5543f80,0xa5543f80,0xa5543f80,0x248dbf80,0x248dbf80,0x248dbf80,0x248dbf80,0x3f80250d,0x3f80250d,0x3f80250d,0x3f80250d,
0xbf800000,0xbf800000,0xbf800000,0xbf800000,0x3f80250d,0x3f80250d,0x3f80250d,0x3f80250d,0xbf800000,0xbf800000,0xbf800000,0xbf800000,
0x3f80250d,0x3f80250d,0x3f80250d,0x3f80250d,0xbf800000,0xbf800000,0xbf800000,0xbf800000,0x3f80250d,0x3f80250d,0x3f80250d,0x3f80250d,
0xbf800000,0xbf800000,0xbf800000,0xbf800000,0x3ec43f80,0x3f6d248d,0xbec4bf80,0xbf6da554,0xbf6dbf35,0xbec43f35,0x3f6d3f35,0x3ec4bf35,
0x3ec43f80,0x3f6d248d,0xbec4bf80,0xbf6da554,0xbf6dbf35,0xbec43f35,0x3f6d3f35,0x3ec4bf35,0x3ec43f80,0x3f6d248d,0xbec4bf80,0xbf6da554,
0xbf6dbf35,0xbec43f35,0x3f6d3f35,0x3ec4bf35,0x3ec43f80,0x3f6d248d,0xbec4bf80,0xbf6da554,0xbf6dbf35,0xbec43f35,0x3f6d3f35,0x3ec4bf35,
0x3ec4bf35,0xbf6dbf35,0xbec43f35,0x3f6d3f35,0xbf6d0000,0x3ec43f80,0x3f6d250d,0xbec4bf80,0x3ec4bf35,0xbf6dbf35,0xbec43f35,0x3f6d3f35,
0xbf6d0000,0x3ec43f80,0x3f6d250d,0xbec4bf80,0x3ec4bf35,0xbf6dbf35,0xbec43f35,0x3f6d3f35,0xbf6d0000,0x3ec43f80,0x3f6d250d,0xbec4bf80,
0x3ec4bf35,0xbf6dbf35,0xbec43f35,0x3f6d3f35,0xbf6d0000,0x3ec43f80,0x3f6d250d,0xbec4bf80,0x3f353f80,0xbf35bf80,0x3f353f80,0xbf35bf80,
0xbf35a554,0x3f35248d,0xbf35a554,0x3f35248d,0x3f353f80,0xbf35bf80,0x3f353f80,0xbf35bf80,0xbf35a554,0x3f35248d,0xbf35a554,0x3f35248d,
0x3f353f80,0xbf35bf80,0x3f353f80,0xbf35bf80,0xbf35a554,0x3f35248d,0xbf35a554,0x3f35248d,0x3f353f80,0xbf35bf80,0x3f353f80,0xbf35bf80,
0xbf35a554,0x3f35248d,0xbf35a554,0x3f35248d,0xbf35bf80,0x3f353f80,0xbf35bf80,0x3f353f80,0xbf350000,0x3f35250d,0xbf350000,0x3f35250d,
0xbf35bf80,0x3f353f80,0xbf35bf80,0x3f353f80,0xbf350000,0x3f35250d,0xbf350000,0x3f35250d,0xbf35bf80,0x3f353f80,0xbf35bf80,0x3f353f80,
0xbf350000,0x3f35250d,0xbf350000,0x3f35250d,0xbf35bf80,0x3f353f80,0xbf35bf80,0x3f353f80,0xbf350000,0x3f35250d,0xbf350000,0x3f35250d,
0x3f6d3f80,0xbec4a554,0xbf6dbf80,0x3ec4248d,0x3ec43f35,0xbf6dbf35,0xbec4bf35,0x3f6d3f35,0x3f6d3f80,0xbec4a554,0xbf6dbf80,0x3ec4248d,
0x3ec43f35,0xbf6dbf35,0xbec4bf35,0x3f6d3f35,0x3f6d3f80,0xbec4a554,0xbf6dbf80,0x3ec4248d,0x3ec43f35,0xbf6dbf35,0xbec4bf35,0x3f6d3f35,
0x3f6d3f80,0xbec4a554,0xbf6dbf80,0x3ec4248d,0x3ec43f35,0xbf6dbf35,0xbec4bf35,0x3f6d3f35,0xbf6dbf35,0xbec4bf35,0x3f6d3f35,0x3ec43f35,
0xbec40000,0xbf6dbf80,0x3ec4250d,0x3f6d3f80,0xbf6dbf35,0xbec4bf35,0x3f6d3f35,0x3ec43f35,0xbec40000,0xbf6dbf80,0x3ec4250d,0x3f6d3f80,
0xbf6dbf35,0xbec4bf35,0x3f6d3f35,0x3ec43f35,0xbec40000,0xbf6dbf80,0x3ec4250d,0x3f6d3f80,0xbf6dbf35,0xbec4bf35,0x3f6d3f35,0x3ec43f35,
0xbec40000,0xbf6dbf80,0x3ec4250d,0x3f6d3f80,0x3dc93f80,0x3ef13f6d,0x3f463f35,0x3f753ec4,0xbe95bf7b,0xbf22bf55,0xbf62bf0e,0xbf7fbe48,
0x3f7f248d,0x3f62bec4,0x3f22bf35,0x3e95bf6d,0xbf753e48,0xbf463f0e,0xbef13f55,0xbdc93f7b,0xbdc9bf80,0xbef1bf6d,0xbf46bf35,0xbf75bec4,
0x3e953f7b,0x3f223f55,0x3f623f0e,0x3f7f3e48,0xbf7fa554,0xbf623ec4,0xbf223f35,0xbe953f6d,0x3f75be48,0x3f46bf0e,0x3ef1bf55,0x3dc9bf7b,
0x3f75be48,0x3f46bf0e,0x3ef1bf55,0x3dc9bf7b,0xbf7f0000,0xbf623ec4,0xbf223f35,0xbe953f6d,0xbe95bf7b,0xbf22bf55,0xbf62bf0e,0xbf7fbe48,
0x3dc93f80,0x3ef13f6d,0x3f463f35,0x3f753ec4,0xbf753e48,0xbf463f0e,0xbef13f55,0xbdc93f7b,0x3f7f250d,0x3f62bec4,0x3f22bf35,0x3e95bf6d,
0x3e953f7b,0x3f223f55,0x3f623f0e,0x3f7f3e48,0xbdc9bf80,0xbef1bf6d,0xbf46bf35,0xbf75bec4,0x3f62248d,0xbf46bf6d,0xbe953f35,0x3f7f3ec4,
0xbdc93f55,0x3f753e48,0xbf22bf7b,0xbef13f0e,0x3ef13f80,0x3f22bec4,0xbf75bf35,0x3dc93f6d,0xbf7fbf0e,0x3e953f7b,0x3f46be48,0xbf62bf55,
0xbf62a554,0x3f463f6d,0x3e95bf35,0xbf7fbec4,0x3dc9bf55,0xbf75be48,0x3f223f7b,0x3ef1bf0e,0xbef1bf80,0xbf223ec4,0x3f753f35,0xbdc9bf6d,
0x3f7f3f0e,0xbe95bf7b,0xbf463e48,0x3f623f55,0xbf7fbf0e,0x3e953f7b,0x3f46be48,0xbf62bf55,0x3ef13f80,0x3f22bec4,0xbf75bf35,0x3dc93f6d,
0x3dc9bf55,0xbf75be48,0x3f223f7b,0x3ef1bf0e,0xbf620000,0x3f463f6d,0x3e95bf35,0xbf7fbec4,0x3f7f3f0e,0xbe95bf7b,0xbf463e48,0x3f623f55,
0xbef1bf80,0xbf223ec4,0x3f753f35,0xbdc9bf6d,0xbdc93f55,0x3f753e48,0xbf22bf7b,0xbef13f0e,0x3f62250d,0xbf46bf6d,0xbe953f35,0x3f7f3ec4,
0xbf46bf80,0x3f753f6d,0xbf7fbf35,0x3f623ec4,0x3ef1be48,0xbdc93f0e,0xbe95bf55,0x3f223f7b,0xbf22a554,0x3e95bec4,0x3dc93f35,0xbef1bf6d,
0xbf62bf7b,0x3f7f3f55,0xbf75bf0e,0x3f463e48,0x3f463f80,0xbf75bf6d,0x3f7f3f35,0xbf62bec4,0xbef13e48,0x3dc9bf0e,0x3e953f55,0xbf22bf7b,
0x3f22248d,0xbe953ec4,0xbdc9bf35,0x3ef13f6d,0x3f623f7b,0xbf7fbf55,0x3f753f0e,0xbf46be48,0x3f623f7b,0xbf7fbf55,0x3f753f0e,0xbf46be48,
0x3f22250d,0xbe953ec4,0xbdc9bf35,0x3ef13f6d,0x3ef1be48,0xbdc93f0e,0xbe95bf55,0x3f223f7b,0xbf46bf80,0x3f753f6d,0xbf7fbf35,0x3f623ec4,
0xbf62bf7b,0x3f7f3f55,0xbf75bf0e,0x3f463e48,0xbf220000,0x3e95bec4,0x3dc93f35,0xbef1bf6d,0xbef13e48,0x3dc9bf0e,0x3e953f55,0xbf22bf7b,
0x3f463f80,0xbf75bf6d,0x3f7f3f35,0xbf62bec4,0xbe95a554,0xbf7fbf6d,0xbef1bf35,0x3f223ec4,0xbf46bf0e,0xbf62bf7b,0x3dc9be48,0x3f753f55,
0xbf75bf80,0xbdc9bec4,0x3f623f35,0x3f463f6d,0xbf22bf55,0x3ef13e48,0x3f7f3f7b,0x3e953f0e,0x3e95248d,0x3f7f3f6d,0x3ef13f35,0xbf22bec4,
0x3f463f0e,0x3f623f7b,0xbdc93e48,0xbf75bf55,0x3f753f80,0x3dc93ec4,0xbf62bf35,0xbf46bf6d,0x3f223f55,0xbef1be48,0xbf7fbf7b,0xbe95bf0e,
0xbf22bf55,0x3ef13e48,0x3f7f3f7b,0x3e953f0e,0xbf75bf80,0xbdc9bec4,0x3f623f35,0x3f463f6d,0x3f463f0e,0x3f623f7b,0xbdc93e48,0xbf75bf55,
0x3e95250d,0x3f7f3f6d,0x3ef13f35,0xbf22bec4,0x3f223f55,0xbef1be48,0xbf7fbf7b,0xbe95bf0e,0x3f753f80,0x3dc93ec4,0xbf62bf35,0xbf46bf6d,
0xbf46bf0e,0xbf62bf7b,0x3dc9be48,0x3f753f55,0xbe950000,0xbf7fbf6d,0xbef1bf35,0x3f223ec4,0x3e483f80,0x3f553f35,0x3f7b248d,0x3f0ebf35,
0xbf0ebf6d,0xbf7bbec4,0xbf553ec4,0xbe483f6d,0xbe48bf80,0xbf55bf35,0xbf7ba554,0xbf0e3f35,0x3f0e3f6d,0x3f7b3ec4,0x3f55bec4,0x3e48bf6d,
0x3e483f80,0x3f553f35,0x3f7b248d,0x3f0ebf35,0xbf0ebf6d,0xbf7bbec4,0xbf553ec4,0xbe483f6d,0xbe48bf80,0xbf55bf35,0xbf7ba554,0xbf0e3f35,
0x3f0e3f6d,0x3f7b3ec4,0x3f55bec4,0x3e48bf6d,0x3f55bec4,0x3e48bf6d,0xbf0ebf6d,0xbf7bbec4,0xbf7b0000,0xbf0e3f35,0x3e483f80,0x3f553f35,
0xbf553ec4,0xbe483f6d,0x3f0e3f6d,0x3f7b3ec4,0x3f7b250d,0x3f0ebf35,0xbe48bf80,0xbf55bf35,0x3f55bec4,0x3e48bf6d,0xbf0ebf6d,0xbf7bbec4,
0xbf7b0000,0xbf0e3f35,0x3e483f80,0x3f553f35,0xbf553ec4,0xbe483f6d,0x3f0e3f6d,0x3f7b3ec4,0x3f7b250d,0x3f0ebf35,0xbe48bf80,0xbf55bf35,
0xbf0ebf80,0xbe483f35,0x3f55248d,0xbf7bbf35,0x3f7b3ec4,0xbf55bf6d,0x3e483f6d,0x3f0ebec4,0x3f0e3f80,0x3e48bf35,0xbf55a554,0x3f7b3f35,
0xbf7bbec4,0x3f553f6d,0xbe48bf6d,0xbf0e3ec4,0xbf0ebf80,0xbe483f35,0x3f55248d,0xbf7bbf35,0x3f7b3ec4,0xbf55bf6d,0x3e483f6d,0x3f0ebec4,
0x3f0e3f80,0x3e48bf35,0xbf55a554,0x3f7b3f35,0xbf7bbec4,0x3f553f6d,0xbe48bf6d,0xbf0e3ec4,0x3e483f6d,0x3f0ebec4,0xbf7bbec4,0x3f553f6d,
0x3f55250d,0xbf7bbf35,0x3f0e3f80,0x3e48bf35,0xbe48bf6d,0xbf0e3ec4,0x3f7b3ec4,0xbf55bf6d,0xbf550000,0x3f7b3f35,0xbf0ebf80,0xbe483f35,
0x3e483f6d,0x3f0ebec4,0xbf7bbec4,0x3f553f6d,0x3f55250d,0xbf7bbf35,0x3f0e3f80,0x3e48bf35,0xbe48bf6d,0xbf0e3ec4,0x3f7b3ec4,0xbf55bf6d,
0xbf550000,0x3f7b3f35,0xbf0ebf80,0xbe483f35,0x3f553f80,0xbf7bbf35,0x3f0e248d,0x3e483f35,0xbe483ec4,0xbf0ebf6d,0x3f7b3f6d,0xbf55bec4,
0xbf55bf80,0x3f7b3f35,0xbf0ea554,0xbe48bf35,0x3e48bec4,0x3f0e3f6d,0xbf7bbf6d,0x3f553ec4,0x3f553f80,0xbf7bbf35,0x3f0e248d,0x3e483f35,
0xbe483ec4,0xbf0ebf6d,0x3f7b3f6d,0xbf55bec4,0xbf55bf80,0x3f7b3f35,0xbf0ea554,0xbe48bf35,0x3e48bec4,0x3f0e3f6d,0xbf7bbf6d,0x3f553ec4,
0xbf7bbf6d,0x3f553ec4,0xbe483ec4,0xbf0ebf6d,0xbf0e0000,0xbe48bf35,0x3f553f80,0xbf7bbf35,0x3f7b3f6d,0xbf55bec4,0x3e48bec4,0x3f0e3f6d,
0x3f0e250d,0x3e483f35,0xbf55bf80,0x3f7b3f35,0xbf7bbf6d,0x3f553ec4,0xbe483ec4,0xbf0ebf6d,0xbf0e0000,0xbe48bf35,0x3f553f80,0xbf7bbf35,
0x3f7b3f6d,0xbf55bec4,0x3e48bec4,0x3f0e3f6d,0x3f0e250d,0x3e483f35,0xbf55bf80,0x3f7b3f35,0xbf7bbf80,0xbf0ebf35,0x3e48248d,0x3f553f35,
0xbf55bf6d,0xbe48bec4,0x3f0e3ec4,0x3f7b3f6d,0x3f7b3f80,0x3f0e3f35,0xbe48a554,0xbf55bf35,0x3f553f6d,0x3e483ec4,0xbf0ebec4,0xbf7bbf6d,
0xbf7bbf80,0xbf0ebf35,0x3e48248d,0x3f553f35,0xbf55bf6d,0xbe48bec4,0x3f0e3ec4,0x3f7b3f6d,0x3f7b3f80,0x3f0e3f35,0xbe48a554,0xbf55bf35,
0x3f553f6d,0x3e483ec4,0xbf0ebec4,0xbf7bbf6d,0x3f0e3ec4,0x3f7b3f6d,0x3f553f6d,0x3e483ec4,0x3e48250d,0x3f553f35,0x3f7b3f80,0x3f0e3f35,
0xbf0ebec4,0xbf7bbf6d,0xbf55bf6d,0xbe48bec4,0xbe480000,0xbf55bf35,0xbf7bbf80,0xbf0ebf35,0x3f0e3ec4,0x3f7b3f6d,0x3f553f6d,0x3e483ec4,
0x3e48250d,0x3f553f35,0x3f7b3f80,0x3f0e3f35,0xbf0ebec4,0xbf7bbf6d,0xbf55bf6d,0xbe48bec4,0xbe480000,0xbf55bf35,0xbf7bbf80,0xbf0ebf35,
0x3e953f80,0x3f7f3ec4,0x3ef1bf35,0xbf22bf6d,0xbf46bf55,0xbf623e48,0x3dc93f7b,0x3f753f0e,0xbf75a554,0xbdc93f6d,0x3f623f35,0x3f46bec4,
0x3f22bf0e,0xbef1bf7b,0xbf7fbe48,0xbe953f55,0xbe95bf80,0xbf7fbec4,0xbef13f35,0x3f223f6d,0x3f463f55,0x3f62be48,0xbdc9bf7b,0xbf75bf0e,
0x3f75248d,0x3dc9bf6d,0xbf62bf35,0xbf463ec4,0xbf223f0e,0x3ef13f7b,0x3f7f3e48,0x3e95bf55,0x3f22bf0e,0xbef1bf7b,0xbf7fbe48,0xbe953f55,
0xbf750000,0xbdc93f6d,0x3f623f35,0x3f46bec4,0x3f463f55,0x3f62be48,0xbdc9bf7b,0xbf75bf0e,0xbe95bf80,0xbf7fbec4,0xbef13f35,0x3f223f6d,
0xbf223f0e,0x3ef13f7b,0x3f7f3e48,0x3e95bf55,0x3f75250d,0x3dc9bf6d,0xbf62bf35,0xbf463ec4,0xbf46bf55,0xbf623e48,0x3dc93f7b,0x3f753f0e,
0x3e953f80,0x3f7f3ec4,0x3ef1bf35,0xbf22bf6d,0xbf46a554,0x3f753ec4,0xbf7fbf35,0x3f623f6d,0xbef1bf7b,0x3dc93f55,0x3e95bf0e,0xbf223e48,
0x3f223f80,0xbe95bf6d,0xbdc93f35,0x3ef1bec4,0xbf62be48,0x3f7f3f0e,0xbf75bf55,0x3f463f7b,0x3f46248d,0xbf75bec4,0x3f7f3f35,0xbf62bf6d,
0x3ef13f7b,0xbdc9bf55,0xbe953f0e,0x3f22be48,0xbf22bf80,0x3e953f6d,0x3dc9bf35,0xbef13ec4,0x3f623e48,0xbf7fbf0e,0x3f753f55,0xbf46bf7b,
0x3f623e48,0xbf7fbf0e,0x3f753f55,0xbf46bf7b,0xbf22bf80,0x3e953f6d,0x3dc9bf35,0xbef13ec4,0xbef1bf7b,0x3dc93f55,0x3e95bf0e,0xbf223e48,
0xbf460000,0x3f753ec4,0xbf7fbf35,0x3f623f6d,0xbf62be48,0x3f7f3f0e,0xbf75bf55,0x3f463f7b,0x3f223f80,0xbe95bf6d,0xbdc93f35,0x3ef1bec4,
0x3ef13f7b,0xbdc9bf55,0xbe953f0e,0x3f22be48,0x3f46250d,0xbf75bec4,0x3f7f3f35,0xbf62bf6d,0xbf62bf80,0x3f463ec4,0x3e953f35,0xbf7fbf6d,
0xbdc9bf0e,0x3f753f7b,0xbf22be48,0xbef1bf55,0x3ef1248d,0x3f223f6d,0xbf75bf35,0x3dc9bec4,0x3f7f3f55,0xbe953e48,0xbf46bf7b,0x3f623f0e,
0x3f623f80,0xbf46bec4,0xbe95bf35,0x3f7f3f6d,0x3dc93f0e,0xbf75bf7b,0x3f223e48,0x3ef13f55,0xbef1a554,0xbf22bf6d,0x3f753f35,0xbdc93ec4,
0xbf7fbf55,0x3e95be48,0x3f463f7b,0xbf62bf0e,0x3f7f3f55,0xbe953e48,0xbf46bf7b,0x3f623f0e,0x3ef1250d,0x3f223f6d,0xbf75bf35,0x3dc9bec4,
0x3dc93f0e,0xbf75bf7b,0x3f223e48,0x3ef13f55,0x3f623f80,0xbf46bec4,0xbe95bf35,0x3f7f3f6d,0xbf7fbf55,0x3e95be48,0x3f463f7b,0xbf62bf0e,
0xbef10000,0xbf22bf6d,0x3f753f35,0xbdc93ec4,0xbdc9bf0e,0x3f753f7b,0xbf22be48,0xbef1bf55,0xbf62bf80,0x3f463ec4,0x3e953f35,0xbf7fbf6d,
0x3dc9248d,0x3ef13ec4,0x3f463f35,0x3f753f6d,0x3e953e48,0x3f223f0e,0x3f623f55,0x3f7f3f7b,0xbf7fbf80,0xbf62bf6d,0xbf22bf35,0xbe95bec4,
0xbf75bf7b,0xbf46bf55,0xbef1bf0e,0xbdc9be48,0xbdc9a554,0xbef1bec4,0xbf46bf35,0xbf75bf6d,0xbe95be48,0xbf22bf0e,0xbf62bf55,0xbf7fbf7b,
0x3f7f3f80,0x3f623f6d,0x3f223f35,0x3e953ec4,0x3f753f7b,0x3f463f55,0x3ef13f0e,0x3dc93e48,0x3f753f7b,0x3f463f55,0x3ef13f0e,0x3dc93e48,
0x3f7f3f80,0x3f623f6d,0x3f223f35,0x3e953ec4,0x3e953e48,0x3f223f0e,0x3f623f55,0x3f7f3f7b,0x3dc9250d,0x3ef13ec4,0x3f463f35,0x3f753f6d,
0xbf75bf7b,0xbf46bf55,0xbef1bf0e,0xbdc9be48,0xbf7fbf80,0xbf62bf6d,0xbf22bf35,0xbe95bec4,0xbe95be48,0xbf22bf0e,0xbf62bf55,0xbf7fbf7b,
0xbdc90000,0xbef1bec4,0xbf46bf35,0xbf75bf6d,
};

constexpr int C20_SBO = 44 * 16;
constexpr int C20_BYTES = 5 * C20_SBO;

__device__ __forceinline__ void tma_load_4d(uint32_t dst, const CUtensorMap* tm, uint32_t bar, int c0, int c1, int c2, int c3) {
    asm volatile("cp.async.bulk.tensor.4d.shared::cluster.global.mbarrier::complete_tx::bytes [%0], [%1, {%3, %4, %5, %6}], [%2];"
                 ::"r"(dst), "l"(tm), "r"(bar), "r"(c0), "r"(c1), "r"(c2), "r"(c3) : "memory");
}
__device__ __forceinline__ void named_bar_arrive(int id, int n) { asm volatile("bar.arrive %0, %1;" ::"r"(id), "r"(n) : "memory"); }
__device__ __forceinline__ uint32_t hsub2_bf16(uint32_t a, uint32_t b) {
    __nv_bfloat162 r = __hsub2(*reinterpret_cast<__nv_bfloat162*>(&a), *reinterpret_cast<__nv_bfloat162*>(&b));
    return *reinterpret_cast<uint32_t*>(&r);
}
__device__ __forceinline__ uint32_t hadd2_bf16(uint32_t a, uint32_t b) {
    __nv_bfloat162 r = __hadd2(*reinterpret_cast<__nv_bfloat162*>(&a), *reinterpret_cast<__nv_bfloat162*>(&b));
    return *reinterpret_cast<uint32_t*>(&r);
}
__device__ __forceinline__ void load_a32(uint32_t (&afr)[4][4], int wtid, bool inverse) {
#pragma unroll
    for (int kap = 0; kap < 4; kap++) {
        const uint4 v = __ldg(reinterpret_cast<const uint4*>(T_A32) + kap * 128 + wtid);
        afr[kap][0] = v.x; afr[kap][1] = inverse ? v.z : v.y; afr[kap][2] = inverse ? v.y : v.z; afr[kap][3] = v.w;
    }
}
__device__ __forceinline__ void ln_row_packed(uint32_t (&w)[10]) {
    float s0 = 0.f, s1 = 0.f, q0 = 0.f, q1 = 0.f;
#pragma unroll
    for (int i = 0; i < 10; i++) {
        const float a = bf_lo(w[i]), b = bf_hi(w[i]);
        s0 += a; q0 = fmaf(a, a, q0);
        s1 += b; q1 = fmaf(b, b, q1);
    }
    float s = s0 + s1, q = q0 + q1;
#pragma unroll
    for (int o = 16; o > 0; o >>= 1) { s += __shfl_xor_sync(0xffffffffu, s, o); q += __shfl_xor_sync(0xffffffffu, q, o); }
    const float mean = s * (1.0f / 640.0f);
    const float var = fmaxf(fmaf(-mean, mean, q * (1.0f / 640.0f)), 0.0f);
    float sq, rinv;
    asm("sqrt.approx.ftz.f32 %0, %1;" : "=f"(sq) : "f"(round_bf16(round_bf16(var) + 1e-5f)));
    asm("rcp.approx.ftz.f32 %0, %1;" : "=f"(rinv) : "f"(round_bf16(sq)));
    const float mean_b = round_bf16(mean);
    const uint32_t m2 = pack_bf16(mean_b, mean_b);
#pragma unroll
    for (int i = 0; i < 10; i++) {
        const uint32_t d = hsub2_bf16(w[i], m2);
        w[i] = pack_bf16(bf_lo(d) * rinv, bf_hi(d) * rinv);
    }
}

constexpr int K2_STAGGER = 350;
struct FftMaps { CUtensorMap wr, wi, v; };

constexpr int K1_SBO = 1024 + 32;
constexpr int K1_BT = 10 * K1_SBO;
constexpr int K1_OFF_C = 2 * K1_BT;
constexpr int K1_OFF_Z = 24704;
constexpr int K1_ZPL = 11776 + 64;
constexpr int K1_OFF_WR = K1_OFF_Z + 2 * 11904;
constexpr int K1_OFF_WT = ((K1_OFF_WR + 4 * 5376 + 511) / 512) * 512;
constexpr int K1_OFF_BAR = K1_OFF_WT + 324 * 64;
constexpr int K1_SMEM = K1_OFF_BAR + 64 + 1024;
__global__ void __launch_bounds__(512, 1) k1_ln_fft(const bf16* __restrict__ x, const __grid_constant__ FftMaps tm) {
    extern __shared__ uint8_t smem_raw[];
    const uint32_t sbase = (smem_u32(smem_raw) + 1023) & ~1023u;
    const int tid = threadIdx.x, warp = tid >> 5, lane = tid & 31;
    const int b = blockIdx.x;
    pdl_launch();
    const int a = b >> 5, p2 = b & 31;
    const int srow = 64 * (8 * a + (warp >> 1)) + 2 * p2 + (warp & 1);
    uint32_t w[10];
#pragma unroll
    for (int i = 0; i < 5; i++) {
        const uint2 v = __ldg(reinterpret_cast<const uint2*>(x + srow * 640) + lane + 32 * i);
        w[2 * i] = v.x; w[2 * i + 1] = v.y;
    }
    const uint32_t bar = sbase + K1_OFF_BAR;
    if (tid == 256) {
        mbar_init(bar, 1);
        fence_mbar_init();
    }
    if (tid >= 256 && tid < 256 + 220) {
        const uint4 v = __ldg(reinterpret_cast<const uint4*>(T_C20) + (tid - 256));
        asm volatile("st.shared.v4.b32 [%0], {%1, %2, %3, %4};" ::"r"(sbase + K1_OFF_C + (tid - 256) * 16), "r"(v.x), "r"(v.y), "r"(v.z), "r"(v.w) : "memory");
    }
    if (b == 1 && tid < 96) g_flags[tid * 32] = 0;
    if (b == 2 && tid < 128) g_flags[96 * 32 + tid] = 0;
    const int wg = warp >> 2, w4 = warp & 3, wtid = tid & 127;
    const int g = lane >> 2, t = lane & 3;
    uint32_t afr[4][4];
    float4 tw[5];
    if (wg < 2) {
        load_a32(afr, wtid, false);
#pragma unroll
        for (int j = 0; j < 5; j++) tw[j] = __ldg(reinterpret_cast<const float4*>(T_TW640) + j * 128 + wtid);
    }
    uint32_t a_b[5];
    {
        const int j8 = warp >> 1, c = warp & 1;
        const uint32_t tile = sbase + (j8 >> 2) * K1_BT;
        const int pl = j8 & 3;
#pragma unroll
        for (int i = 0; i < 5; i++) {
            const int q = lane + 32 * i;
            const int a1 = q / 5, a2 = 4 * (q % 5);
            const int k = 16 * (a1 >> 3) + 8 * c + (a1 & 7);
            const int n = 20 * pl + a2;
            a_b[i] = tile + (n >> 3) * K1_SBO + k * 16 + (n & 7) * 2;
            asm volatile("" : "+r"(a_b[i]));
        }
    }
    ln_row_packed(w);
#pragma unroll
    for (int i = 0; i < 5; i++) asm volatile("st.shared.v2.b32 [%0], {%1, %2};" ::"r"(a_b[i]), "r"(w[2 * i]), "r"(w[2 * i + 1]) : "memory");
    fence_proxy_async_smem();
    if (wg >= 2) {
        named_bar_arrive(1, 512);
        if (tid == 256) {
            const int wq = b >> 5, gq = (b & 31) >> 2, tq = b & 3;
            const int c0 = gq * 320;
            mbar_expect_tx(bar, 4 * 5376);
            tma_load_4d(sbase + K1_OFF_WR, &tm.wr, bar, c0, wq, 4 * tq, 0);
            tma_load_4d(sbase + K1_OFF_WR + 5376, &tm.wr, bar, c0 + 160, wq, 4 * tq, 0);
            tma_load_4d(sbase + K1_OFF_WR + 2 * 5376, &tm.wi, bar, c0, wq, 4 * tq, 0);
            tma_load_4d(sbase + K1_OFF_WR + 3 * 5376, &tm.wi, bar, c0 + 160, wq, 4 * tq, 0);
        }
        named_bar_sync(2, 256);
        mbar_wait(bar, 0);
        for (int kd = tid - 256; kd < 321; kd += 256) {
            const int pos = kd + ((b & 31) >> 2);
            const int half = pos >= 160;
            const uint32_t src = sbase + K1_OFF_WR + half * 5376 + (pos - 160 * half) * 2;
            uint32_t v[16];
#pragma unroll
            for (int j = 0; j < 16; j++) {
                uint16_t re, im;
                asm volatile("ld.shared.u16 %0, [%1];" : "=h"(re) : "r"(src + j * 336));
                asm volatile("ld.shared.u16 %0, [%1];" : "=h"(im) : "r"(src + 2 * 5376 + j * 336));
                v[j] = (uint32_t)re | ((uint32_t)im << 16);
            }
            const uint32_t dst = sbase + K1_OFF_WT + kd * 64;
            const int sw = (kd >> 1) & 3;
#pragma unroll
            for (int q = 0; q < 4; q++)
                asm volatile("st.shared.v4.b32 [%0], {%1, %2, %3, %4};" ::"r"(dst + ((q ^ sw) << 4)), "r"(v[4 * q]), "r"(v[4 * q + 1]), "r"(v[4 * q + 2]), "r"(v[4 * q + 3]) : "memory");
        }
        __syncwarp();
        for (int kd0 = (tid - 256) & ~31; kd0 < 321; kd0 += 256) {
#pragma unroll
            for (int i = 0; i < 4; i++) {
                const int kd = kd0 + 8 * i + (lane >> 2);
                if (kd < 321) {
                    uint4 v;
                    asm volatile("ld.shared.v4.b32 {%0, %1, %2, %3}, [%4];" : "=r"(v.x), "=r"(v.y), "=r"(v.z), "=r"(v.w)
                                 : "r"(sbase + K1_OFF_WT + kd * 64 + (((lane & 3) ^ ((kd >> 1) & 3)) << 4)) : "memory");
                    reinterpret_cast<uint4*>(g_Wt)[(kd * 128 + b) * 4 + (lane & 3)] = v;
                }
            }
        }
        return;
    }
    named_bar_sync(1, 512);
    float acc[40];
    {
        const uint32_t tile = sbase + wg * K1_BT;
        wgmma_fence();
#pragma unroll
        for (int kap = 0; kap < 4; kap++) wgmma_rs_bf16_n80<1>(acc, afr[kap], make_desc(tile + kap * 256, 128, K1_SBO, 0), kap > 0);
        wgmma_commit();
        wgmma_wait<0>();
        fence_regs<40>(acc);
    }
    uint32_t a2f[5][4];
#pragma unroll
    for (int j8 = 0; j8 < 10; j8++) {
        const float4 tt = tw[j8 % 5];
        const float r0 = acc[4 * j8], r1 = acc[4 * j8 + 1], i0 = acc[4 * j8 + 2], i1 = acc[4 * j8 + 3];
        a2f[j8 >> 1][(j8 & 1) * 2 + 0] = pack_bf16(r0 * tt.x + i0 * tt.y, r1 * tt.z + i1 * tt.w);
        a2f[j8 >> 1][(j8 & 1) * 2 + 1] = pack_bf16(i0 * tt.x - r0 * tt.y, i1 * tt.z - r1 * tt.w);
    }
    float acc2[4][20];
    {
        const uint32_t sC = sbase + K1_OFF_C;
        wgmma_fence();
#pragma unroll
        for (int pl = 0; pl < 4; pl++) {
            wgmma_rs_bf16_n40<1>(acc2[pl], a2f[pl], make_desc(sC + (12 - 4 * pl) * 16, 128, C20_SBO, 0), 0);
            wgmma_rs_bf16_n40<1>(acc2[pl], a2f[pl + 1], make_desc(sC + (28 - 4 * pl) * 16, 128, C20_SBO, 0), 1);
        }
        wgmma_commit();
        wgmma_wait<0>();
#pragma unroll
        for (int pl = 0; pl < 4; pl++) fence_regs<20>(acc2[pl]);
    }
    {
        const int k1 = 8 * w4 + g;
        const uint32_t zre = sbase + K1_OFF_Z + 8 * wg + (p2 & 1) * K1_ZPL, zim = sbase + K1_OFF_Z + 8 * wg + ((p2 & 1) ^ 1) * K1_ZPL;
#pragma unroll
        for (int j = 0; j < 5; j++) {
            const int k = k1 + 32 * (4 * j + t);
            float zr[4], zi[4];
#pragma unroll
            for (int pl = 0; pl < 4; pl++) {
                zr[pl] = acc2[pl][4 * j] + acc2[pl][4 * j + 3];
                zi[pl] = acc2[pl][4 * j + 2] - acc2[pl][4 * j + 1];
            }
            const uint32_t r0 = pack_bf16(zr[0], zr[1]), r1 = pack_bf16(zr[2], zr[3]);
            uint32_t i0 = pack_bf16(zi[0], zi[1]), i1 = pack_bf16(zi[2], zi[3]);
            const bool minus = k > 320;
            const int e = minus ? 324 + 640 - k : k;
            const uint32_t eo = e * 16 + ((e >> 5) & 1) * 64 + (e >> 6) * 128;
            if (minus) { i0 ^= 0x80008000u; i1 ^= 0x80008000u; }
            asm volatile("st.shared.v2.b32 [%0], {%1, %2};" ::"r"(zre + eo), "r"(r0), "r"(r1) : "memory");
            asm volatile("st.shared.v2.b32 [%0], {%1, %2};" ::"r"(zim + eo), "r"(i0), "r"(i1) : "memory");
            if ((j == 0 && k == 0) || (j == 2 && k == 320)) {
                const int e2 = 324 + k;
                const uint32_t eo2 = e2 * 16 + ((e2 >> 5) & 1) * 64 + (e2 >> 6) * 128;
                asm volatile("st.shared.v2.b32 [%0], {%1, %2};" ::"r"(zre + eo2), "r"(r0), "r"(r1) : "memory");
                asm volatile("st.shared.v2.b32 [%0], {%1, %2};" ::"r"(zim + eo2), "r"(i0 ^ 0x80008000u), "r"(i1 ^ 0x80008000u) : "memory");
            }
        }
    }
    named_bar_sync(3, 256);
    {
        uint8_t* zdst = reinterpret_cast<uint8_t*>(g_Z) + p2 * 128 + ((a ^ ((p2 & 7) >> 1)) << 5) + (tid & 1) * 16;
#pragma unroll
        for (int i = 0; i < 6; i++) {
            const int e = (tid >> 1) + 128 * i;
            const int sg = e >= 324, kd = e - 324 * sg;
            if (kd < 321 && e < 648) {
                uint4 v;
                asm volatile("ld.shared.v4.b32 {%0, %1, %2, %3}, [%4];" : "=r"(v.x), "=r"(v.y), "=r"(v.z), "=r"(v.w)
                             : "r"(sbase + K1_OFF_Z + (tid & 1) * K1_ZPL + e * 16 + ((e >> 5) & 1) * 64 + (e >> 6) * 128) : "memory");
                *reinterpret_cast<uint4*>(zdst + kd * 8192 + sg * 4096) = v;
            }
        }
    }
}

constexpr int K2_SMEM = 1024 + 16384 + 6 * 8192 + 1024;
__global__ void __launch_bounds__(384, 1) k2_colfft(const uint8_t* __restrict__ w1, const uint8_t* __restrict__ w3, const uint8_t* __restrict__ w2) {
    extern __shared__ uint8_t smem_raw[];
    const uint32_t sbase = (smem_u32(smem_raw) + 1023) & ~1023u;
    const uint32_t sC = sbase;
    const uint32_t sBall = sbase + 16384;
    const uint32_t sWall = sBall + 3 * 8192;
    const uint32_t sMisc = sWall + 3 * 8192;
    const int tid = threadIdx.x, wg = tid >> 7, wtid = tid & 127, warp = wtid >> 5, lane = tid & 31;
    pdl_launch();
    const int kd = 3 * blockIdx.x + wg;
    const uint32_t sB = sBall + wg * 8192;
    const uint32_t bar = sMisc + 8 * wg, barC = sMisc + 32;
    if (tid == 0) {
        for (int i = 0; i < 3; i++) { mbar_init(sMisc + 8 * i, 1); mbar_init(sMisc + 40 + 8 * i, 1); }
        mbar_init(barC, 1);
        fence_mbar_init();
        mbar_expect_tx(barC, 16384);
        bulk_load(sC, T_C64, 16384, barC);
    }
    uint32_t afr[4][4];
    load_a32(afr, wtid, false);
    float4 tw[8];
#pragma unroll
    for (int i = 0; i < 8; i++) tw[i] = __ldg(reinterpret_cast<const float4*>(T_TW2048) + i * 128 + wtid);
    __syncthreads();
    pdl_wait();
    if (tid == 0) {
        auto ldz = [&](int u) { mbar_expect_tx(sMisc + 8 * u, 8192); bulk_load(sBall + u * 8192, reinterpret_cast<const uint8_t*>(g_Z) + (3 * blockIdx.x + u) * 8192, 8192, sMisc + 8 * u); };
        auto ldw = [&](int u) { mbar_expect_tx(sMisc + 40 + 8 * u, 8192); bulk_load(sWall + u * 8192, reinterpret_cast<const uint8_t*>(g_Wt) + (3 * blockIdx.x + u) * 8192, 8192, sMisc + 40 + 8 * u); };
        ldz(0); ldz(1); ldw(0); ldz(2); ldw(1); ldw(2);
    }
    {
        const int li = blockIdx.x * 144 + wtid;
        const uint8_t* wsrc = wg == 0 ? w1 : wg == 1 ? w3 : w2;
        if (li < 15360) asm volatile("prefetch.global.L2 [%0];" ::"l"(wsrc + (size_t)li * 128));
        if (wtid < 16 && li + 128 < 15360) asm volatile("prefetch.global.L2 [%0];" ::"l"(wsrc + (size_t)(li + 128) * 128));
    }
    mbar_wait(bar, 0);
    { const long long t0 = clock64(); while (clock64() - t0 < (long long)wg * K2_STAGGER) { } }
    uint32_t af[4][4];
    {
        float acc[32];
        wgmma_fence();
#pragma unroll
        for (int kap = 0; kap < 4; kap++) wgmma_rs_bf16_n64<0>(acc, afr[kap], make_desc(sB + kap * 32, 16, 1024, 1), kap > 0);
        wgmma_commit();
        wgmma_wait<0>();
        fence_regs<32>(acc);
#pragma unroll
        for (int kap = 0; kap < 4; kap++)
#pragma unroll
            for (int h = 0; h < 2; h++) {
                const float pr = acc[4 * kap + h], pi = acc[4 * kap + 2 + h];
                const float qr = acc[4 * (kap + 4) + h], qi = acc[4 * (kap + 4) + 2 + h];
                const float y0r = pr + qr, y0i = pi + qi, y1r = pi - qi, y1i = qr - pr;
                const float4 tt = tw[2 * kap + h];
                af[kap][2 * h + 0] = pack_bf16(y0r * tt.x + y0i * tt.y, y1r * tt.z + y1i * tt.w);
                af[kap][2 * h + 1] = pack_bf16(y0i * tt.x - y0r * tt.y, y1i * tt.z - y1r * tt.w);
            }
    }
    float acc2[64];
    mbar_wait(barC, 0);
    wgmma_fence();
#pragma unroll
    for (int kap = 0; kap < 4; kap++) wgmma_rs_bf16_n128<0>(acc2, af[kap], make_desc(sC + kap * 32, 16, 1024, 1), kap > 0);
    wgmma_commit();
    wgmma_wait<0>();
    fence_regs<64>(acc2);
    {
        mbar_wait(sMisc + 40 + 8 * wg, 0);
        uint32_t wf[16];
#pragma unroll
        for (int q = 0; q < 4; q++)
            asm volatile("ld.shared.v4.b32 {%0, %1, %2, %3}, [%4];" : "=r"(wf[4 * q]), "=r"(wf[4 * q + 1]), "=r"(wf[4 * q + 2]), "=r"(wf[4 * q + 3])
                         : "r"(sWall + wg * 8192 + wtid * 64 + q * 16));
#pragma unroll
        for (int kap = 0; kap < 4; kap++)
#pragma unroll
            for (int h = 0; h < 2; h++) {
                float gr[2], gi[2];
#pragma unroll
                for (int e = 0; e < 2; e++) {
                    const int j = 4 * kap + 2 * h + e;
                    const float xr = acc2[4 * j] + acc2[4 * j + 3], xi = acc2[4 * j + 2] - acc2[4 * j + 1];
                    const float wr_ = bf_lo(wf[j]), wi_ = bf_hi(wf[j]);
                    gr[e] = xr * wr_ - xi * wi_;
                    gi[e] = xr * wi_ + xi * wr_;
                }
                af[kap][2 * h + 0] = pack_bf16(gr[0], gr[1]);
                af[kap][2 * h + 1] = pack_bf16(gi[0], gi[1]);
            }
    }
    wgmma_fence();
#pragma unroll
    for (int kap = 0; kap < 4; kap++) wgmma_rs_bf16_n128<0>(acc2, af[kap], make_desc(sC + kap * 32, 16, 1024, 1), kap > 0);
    wgmma_commit();
    wgmma_wait<0>();
    fence_regs<64>(acc2);
    {
        uint32_t ure[8], uim[8];
#pragma unroll
        for (int jp = 0; jp < 8; jp++) {
            const int j = 2 * jp;
            const float4 tt = tw[jp];
            const float u0r = acc2[4 * j] - acc2[4 * j + 3], u0i = acc2[4 * j + 2] + acc2[4 * j + 1];
            const float u1r = acc2[4 * j + 4] - acc2[4 * j + 7], u1i = acc2[4 * j + 6] + acc2[4 * j + 5];
            ure[jp] = pack_bf16(u0r * tt.x - u0i * tt.y, u1r * tt.z - u1i * tt.w);
            uim[jp] = pack_bf16(-(u0i * tt.x + u0r * tt.y), -(u1i * tt.z + u1r * tt.w));
        }
        const int tile = lane >> 3, r = lane & 7;
        const int row = 16 * warp + 8 * (tile & 1) + r;
#pragma unroll
        for (int jp = 0; jp < 8; jp += 2) {
            const int chunk = (jp + (tile >> 1)) ^ r;
            stmatrix_x4(sB + row * 128 + chunk * 16, ure[jp], uim[jp], ure[jp + 1], uim[jp + 1]);
        }
    }
    fence_proxy_async_smem();
    named_bar_sync(1 + wg, 128);
    {
        float acc[32];
        wgmma_fence();
#pragma unroll
        for (int kap = 0; kap < 4; kap++) wgmma_rs_bf16_n64<1>(acc, afr[kap], make_desc(sB + kap * 2048, 8192, 1024, 1), kap > 0);
        wgmma_commit();
        wgmma_wait<0>();
        fence_regs<32>(acc);
        uint32_t pr[4], pi[4], mr[4], mi[4];
        const float sp = (kd == 0 || kd == 320) ? 0.0f : 1.0f;
#pragma unroll
        for (int q = 0; q < 4; q++) {
            float vpr[2], vpi[2], vmr[2], vmi[2];
#pragma unroll
            for (int u = 0; u < 2; u++) {
                const int jp = 2 * q + u;
                const float r0r = acc[4 * jp], r1r = acc[4 * jp + 1], r0i = acc[4 * jp + 2], r1i = acc[4 * jp + 3];
                vpr[u] = fmaf(sp, r1i, r0r);
                vpi[u] = fmaf(-sp, r0i, r1r);
                vmr[u] = r0r - r1i;
                vmi[u] = r0i + r1r;
            }
            pr[q] = pack_bf16(vpr[0], vpr[1]); pi[q] = pack_bf16(vpi[0], vpi[1]);
            mr[q] = pack_bf16(vmr[0], vmr[1]); mi[q] = pack_bf16(vmi[0], vmi[1]);
        }
        uint4* dp = reinterpret_cast<uint4*>(g_V) + (kd * 128 + wtid) * 2;
        dp[0] = make_uint4(pr[0], pr[1], pr[2], pr[3]);
        dp[1] = make_uint4(pi[0], pi[1], pi[2], pi[3]);
        if (sp != 0.0f) {
            uint4* dm = reinterpret_cast<uint4*>(g_V) + ((640 - kd) * 128 + wtid) * 2;
            dm[0] = make_uint4(mr[0], mr[1], mr[2], mr[3]);
            dm[1] = make_uint4(mi[0], mi[1], mi[2], mi[3]);
        }
    }
}

constexpr int K3_STAGE = 640 * 32 + 32 * 16;
constexpr int K3_SBO = 1024 + 16;
constexpr int K3_BT = 5248;
constexpr int K3_YP = 1280 + 320 + 80;
constexpr int K3_OFF_B = K3_STAGE;
constexpr int K3_OFF_C = K3_OFF_B + 4 * K3_BT + 128;
constexpr int K3_OFF_Y = K3_OFF_C + C20_BYTES + 64;
constexpr int K3_OFF_BAR = K3_OFF_Y + 16 * K3_YP;
constexpr int K3_SMEM = K3_OFF_BAR + 64 + 128;
__global__ void __launch_bounds__(512, 1) k3_ifft_ln(const bf16* __restrict__ x, const __grid_constant__ FftMaps tm) {
    extern __shared__ __align__(128) uint8_t smem_k3[];
    const uint32_t sbase = (smem_u32(smem_k3) + 127) & ~127u;
    const int tid = threadIdx.x, warp = tid >> 5, lane = tid & 31;
    const int b3 = blockIdx.x;
    const int n1 = b3 >> 2, tq = b3 & 3;
    const int wg = warp >> 2, w4 = warp & 3, wtid = tid & 127;
    pdl_launch();
    const int l_ = warp >> 1;
    const int row = 2 * (32 * n1 + 8 * (l_ >> 1) + 2 * tq + (l_ & 1)) + (warp & 1);
    uint32_t xw[10];
#pragma unroll
    for (int i = 0; i < 5; i++) {
        const uint2 v = __ldg(reinterpret_cast<const uint2*>(x + row * 640) + lane + 32 * i);
        xw[2 * i] = v.x; xw[2 * i + 1] = v.y;
    }
    uint32_t afr[4][4];
#pragma unroll
    for (int kap = 0; kap < 4; kap++) {
        const uint4 v = __ldg(reinterpret_cast<const uint4*>(T_A32I) + kap * 128 + wtid);
        afr[kap][0] = v.x; afr[kap][1] = v.y; afr[kap][2] = v.z; afr[kap][3] = v.w;
    }
    float4 tw[5];
#pragma unroll
    for (int j = 0; j < 5; j++) {
        const float sc = 0.5f / (2048.0f * 640.0f);
        tw[j] = __ldg(reinterpret_cast<const float4*>(T_TW640) + j * 128 + wtid);
        tw[j].x *= sc; tw[j].y *= sc; tw[j].z *= sc; tw[j].w *= sc;
    }
    if (tid < 220) {
        const uint4 v = __ldg(reinterpret_cast<const uint4*>(T_C20) + tid);
        asm volatile("st.shared.v4.b32 [%0], {%1, %2, %3, %4};" ::"r"(sbase + K3_OFF_C + tid * 16), "r"(v.x), "r"(v.y), "r"(v.z), "r"(v.w) : "memory");
    }
    if (tid == 0) {
        for (int i = 0; i < 4; i++) mbar_init(sbase + K3_OFF_BAR + 8 * i, 1);
        fence_mbar_init();
    }
    uint32_t a_ld[3], a_st[3], a_y[3];
    {
        const int i = lane & 7, mq = lane >> 3;
        const uint32_t dtile = sbase + K3_OFF_B + (i >> 1) * K3_BT + ((i >> 1) & 1) * 16 + ((i >> 2) & 1) * 64;
        const int tt = i >> 1, c = i & 1;
#pragma unroll
        for (int it = 0; it < 3; it++) {
            const int task = warp + 16 * it;
            const int k1p = task >> 1, h = task & 1;
            a_ld[it] = sbase + k1p * 1024 + (32 * h + lane) * 16;
            const int n = 20 * (i & 1) + k1p;
            a_st[it] = dtile + (n >> 3) * K3_SBO + (n & 7) * 16 + (4 * h + mq) * 128;
            int id = 4 * it + mq;
            if (id >= 10) id -= 2;
            const int pl = id / 5, j = id % 5;
            const int d0 = 32 * (4 * j + tt) + 8 * w4;
            a_y[it] = sbase + K3_OFF_Y + (2 * (2 * wg + pl) + c) * K3_YP + d0 * 2 + (d0 >> 6) * 32;
            asm volatile("" : "+r"(a_ld[it]), "+r"(a_st[it]), "+r"(a_y[it]));
        }
    }
    __syncthreads();
    pdl_wait();
    if (tid == 0) {
#pragma unroll
        for (int i = 0; i < 4; i++) {
            mbar_expect_tx(sbase + K3_OFF_BAR + 8 * i, 5 * 1024);
            tma_load_4d(sbase + i * 5120, &tm.v, sbase + K3_OFF_BAR + 8 * i, 0, 0, 5 * i, b3);
        }
    }
#pragma unroll
    for (int it = 0; it < 3; it++) {
        const int task = warp + 16 * it;
        if (task < 40) {
            mbar_wait(sbase + K3_OFF_BAR + 8 * (task / 10), 0);
            uint32_t r0, r1, r2, r3;
            ldmatrix_x4_trans(a_ld[it], r0, r1, r2, r3);
            stmatrix_x4(a_st[it], r0, r1, r2, r3);
        }
    }
    fence_proxy_async_smem();
    __syncthreads();
    float acc[20];
    {
        const uint32_t tile = sbase + K3_OFF_B + wg * K3_BT + (wg & 1) * 16 + (wg >> 1) * 64;
        wgmma_fence();
#pragma unroll
        for (int kap = 0; kap < 4; kap++) wgmma_rs_bf16_n40<0>(acc, afr[kap], make_desc(tile + kap * 256, 128, K3_SBO, 0), kap > 0);
        wgmma_commit();
        wgmma_wait<0>();
        fence_regs<20>(acc);
    }
    uint32_t a2f[3][4];
#pragma unroll
    for (int j8 = 0; j8 < 5; j8++) {
        const float4 tt = tw[j8];
        const float r0 = acc[4 * j8], r1 = acc[4 * j8 + 1], i0 = acc[4 * j8 + 2], i1 = acc[4 * j8 + 3];
        a2f[j8 >> 1][(j8 & 1) * 2 + 0] = pack_bf16(r0 * tt.x - i0 * tt.y, r1 * tt.z - i1 * tt.w);
        a2f[j8 >> 1][(j8 & 1) * 2 + 1] = pack_bf16(i0 * tt.x + r0 * tt.y, i1 * tt.z + r1 * tt.w);
    }
    a2f[2][2] = 0u; a2f[2][3] = 0u;
    float acc2[2][20];
    {
        const uint32_t sC = sbase + K3_OFF_C;
        wgmma_fence();
        wgmma_rs_bf16_n40<1>(acc2[0], a2f[0], make_desc(sC + 12 * 16, 128, C20_SBO, 0), 0);
        wgmma_rs_bf16_n40<1>(acc2[1], a2f[1], make_desc(sC + 8 * 16, 128, C20_SBO, 0), 0);
        wgmma_rs_bf16_n40<1>(acc2[0], a2f[1], make_desc(sC + 28 * 16, 128, C20_SBO, 0), 1);
        wgmma_rs_bf16_n40<1>(acc2[1], a2f[2], make_desc(sC + 24 * 16, 128, C20_SBO, 0), 1);
        wgmma_commit();
        wgmma_wait<0>();
        fence_regs<20>(acc2[0]);
        fence_regs<20>(acc2[1]);
    }
    {
        uint32_t yv[10];
#pragma unroll
        for (int pl = 0; pl < 2; pl++)
#pragma unroll
            for (int j = 0; j < 5; j++)
                yv[pl * 5 + j] = pack_bf16(acc2[pl][4 * j] - acc2[pl][4 * j + 3], acc2[pl][4 * j + 2] + acc2[pl][4 * j + 1]);
        stmatrix_x4_trans(a_y[0], yv[0], yv[1], yv[2], yv[3]);
        stmatrix_x4_trans(a_y[1], yv[4], yv[5], yv[6], yv[7]);
        stmatrix_x4_trans(a_y[2], yv[8], yv[9], yv[8], yv[9]);
    }
    __syncthreads();
    {
        uint32_t hw[10];
#pragma unroll
        for (int i = 0; i < 5; i++) {
            const int d0 = 4 * (lane + 32 * i);
            uint2 yv;
            asm volatile("ld.shared.v2.b32 {%0, %1}, [%2];" : "=r"(yv.x), "=r"(yv.y) : "r"(sbase + K3_OFF_Y + warp * K3_YP + d0 * 2 + (d0 >> 6) * 32));
            hw[2 * i] = hadd2_bf16(xw[2 * i], yv.x);
            hw[2 * i + 1] = hadd2_bf16(xw[2 * i + 1], yv.y);
            reinterpret_cast<uint2*>(g_h + row * 640)[lane + 32 * i] = make_uint2(hw[2 * i], hw[2 * i + 1]);
        }
        ln_row_packed(hw);
#pragma unroll
        for (int i = 0; i < 5; i++) reinterpret_cast<uint2*>(g_hn + row * 640)[lane + 32 * i] = make_uint2(hw[2 * i], hw[2 * i + 1]);
    }
}


constexpr int F_NS = 6;
constexpr int F_SLOT = 36864;
constexpr int F_STG_OFF = F_NS * F_SLOT;
constexpr int F_BAR_OFF = F_STG_OFF + 8192;
constexpr int F_SMEM = F_BAR_OFF + 512 + 1024;

__device__ __forceinline__ void tma_load_3d_mc(uint32_t dst, const CUtensorMap* tm, uint32_t bar, int c0, int c1, int c2, uint16_t mask) {
    asm volatile("cp.async.bulk.tensor.3d.shared::cluster.global.mbarrier::complete_tx::bytes.multicast::cluster [%0], [%1, {%3, %4, %5}], [%2], %6;"
                 ::"r"(dst), "l"(tm), "r"(bar), "r"(c0), "r"(c1), "r"(c2), "h"(mask) : "memory");
}
__device__ __forceinline__ uint32_t cluster_ctarank() { uint32_t r; asm volatile("mov.u32 %0, %%cluster_ctarank;" : "=r"(r)); return r; }
__device__ __forceinline__ void arrive_both(uint32_t bar) { mbar_arrive_cluster(bar, 0); mbar_arrive_cluster(bar, 1); }
__device__ __forceinline__ void wait_flag(const unsigned* p, unsigned target) {
    unsigned v;
    int spins = 0;
    do {
        asm volatile("ld.acquire.gpu.global.u32 %0, [%1];" : "=r"(v) : "l"(p) : "memory");
    } while (v < target && ++spins < (1 << 24));
}
__device__ __forceinline__ float silu_mul(float gate, float up) {
    float e, r;
    asm("ex2.approx.ftz.f32 %0, %1;" : "=f"(e) : "f"(gate * -1.4426950408889634f));
    asm("rcp.approx.ftz.f32 %0, %1;" : "=f"(r) : "f"(1.0f + e));
    return gate * up * r;
}
__device__ __forceinline__ float silu_mul_fast(float gate, float up) {
    float t;
    const float a = gate * 0.5f;
    asm("tanh.approx.f32 %0, %1;" : "=f"(t) : "f"(a));
    const float h = a * up;
    return fmaf(h, t, h);
}
__device__ __forceinline__ uint4 quad_transpose(uint32_t r0, uint32_t r1, uint32_t r2, uint32_t r3, int t) {
    const bool o1 = t & 1, o2 = t & 2;
    uint32_t s0 = o1 ? r0 : r1, s1 = o1 ? r2 : r3;
    s0 = __shfl_xor_sync(0xffffffffu, s0, 1);
    s1 = __shfl_xor_sync(0xffffffffu, s1, 1);
    uint32_t a0 = o1 ? s0 : r0, a1 = o1 ? r1 : s0;
    uint32_t b0 = o1 ? s1 : r2, b1 = o1 ? r3 : s1;
    uint32_t u0 = o2 ? a0 : b0, u1 = o2 ? a1 : b1;
    u0 = __shfl_xor_sync(0xffffffffu, u0, 2);
    u1 = __shfl_xor_sync(0xffffffffu, u1, 2);
    uint4 o;
    o.x = o2 ? u0 : a0; o.y = o2 ? u1 : a1; o.z = o2 ? b0 : u0; o.w = o2 ? b1 : u1;
    return o;
}
template <int NG, int UP> __device__ __forceinline__ void silu_guard(float* acc) {
    uint32_t m0 = 0, m1 = 0;
#pragma unroll
    for (int i = 0; i < NG; i += 4) {
        m0 = __vimax3_u32(m0, __float_as_uint(acc[i]), __float_as_uint(acc[i + 1]));
        m1 = __vimax3_u32(m1, __float_as_uint(acc[i + 2]), __float_as_uint(acc[i + 3]));
    }
    if (__builtin_expect(__any_sync(0xffffffffu, max(m0, m1) > 0xC0000000u), 0)) {
#pragma unroll
        for (int i = 0; i < NG; i++) {
            acc[UP + i] = silu_mul(acc[i], acc[UP + i]) * 0.03125f;
            acc[i] = 32.0f;
        }
    }
}
template <int Q, int UP, bool WAIT> __device__ __forceinline__ void epi1_q(float* acc, uint32_t buf, uint32_t woff0, uint32_t woff1, uint32_t bar_free, uint32_t bar_full, int lane) {
    uint32_t lo[4], hi[4];
#pragma unroll
    for (int i = 0; i < 16; i++) { asm volatile("" : "+f"(acc[16 * Q + i])); asm volatile("" : "+f"(acc[UP + 16 * Q + i])); }
#pragma unroll
    for (int i = 0; i < 4; i++) {
        const int b = 16 * Q + 4 * i;
        lo[i] = pack_bf16(silu_mul_fast(acc[b], acc[UP + b]), silu_mul_fast(acc[b + 1], acc[UP + b + 1]));
        hi[i] = pack_bf16(silu_mul_fast(acc[b + 2], acc[UP + b + 2]), silu_mul_fast(acc[b + 3], acc[UP + b + 3]));
    }
    if (WAIT) mbar_wait(bar_free, 0);
    stmatrix_x4(buf + woff0, lo[0], hi[0], lo[1], hi[1]);
    stmatrix_x4(buf + woff1, lo[2], hi[2], lo[3], hi[3]);
    fence_proxy_async_smem();
    __syncwarp();
    if (lane == 0) mbar_arrive(bar_full);
}
__device__ __forceinline__ uint32_t kf_stg(uint32_t sbase, int cw, int n) {
    return n < 3 ? sbase + (3 * cw + n) * F_SLOT + 32768 : n == 3 ? sbase + F_STG_OFF + cw * 4096 : sbase + F_STG_OFF + (n - 4) * 4096;
}

struct KfMaps { CUtensorMap hnA, hnB, w1a, w3a, w1b, w3b, g, w2, gst; };

__global__ void __cluster_dims__(2, 1, 1) __launch_bounds__(384, 1)
kf_ffn(const __grid_constant__ KfMaps tm, bf16* __restrict__ out) {
    extern __shared__ uint8_t smem_raw[];
    const uint32_t sbase = (smem_u32(smem_raw) + 1023) & ~1023u;
    const uint32_t bars = sbase + F_BAR_OFF;
    const uint32_t full = bars, empty = bars + 48, sfree = bars + 96, tfree = bars + 128, sfull = bars + 136, gready = bars + 232;
    const int wg = threadIdx.x >> 7;
    const uint32_t rank = cluster_ctarank();
    const int pair = blockIdx.x >> 1;
    const int ti = 2 * (pair >> 3) + rank;
    const int tj = pair & 7;
    const int kh = tj >> 2, nt = tj & 3;
    if (threadIdx.x == 0) {
        for (int s = 0; s < F_NS; s++) { mbar_init(full + 8 * s, 2); mbar_init(empty + 8 * s, 4); }
        for (int i = 0; i < 12; i++) mbar_init(sfull + 8 * i, 4);
        for (int i = 0; i < 4; i++) mbar_init(sfree + 8 * i, 1);
        mbar_init(tfree, 2);
        for (int i = 0; i < 4; i++) mbar_init(gready + 8 * i, 1);
        fence_mbar_init();
    }
    __syncthreads();
    asm volatile("barrier.cluster.arrive.relaxed.aligned;\nbarrier.cluster.wait.aligned;" ::: "memory");
    if (wg == 0) {
        reg_dealloc<40>();
        const int warp = threadIdx.x >> 5, lane = threadIdx.x & 31;
        if (warp == 0 && lane == 0) {
            for (int q = 0; q < 42; q++) {
                const int s = q % F_NS, use = q / F_NS;
                if (use > 0) mbar_wait(empty + 8 * s, (use - 1) & 1);
                const uint32_t dst = sbase + s * F_SLOT + 16384, fb = full + 8 * s;
                if (q < 20) {
                    mbar_expect_tx(fb, 16384);
                    tma_load_3d_mc(dst + rank * 8192, rank ? &tm.w3a : &tm.w1a, fb, 0, q * 32, 2 * tj, 3);
                } else if (q < 30) {
                    mbar_expect_tx(fb, 16384);
                    tma_load_3d_mc(dst + rank * 8192, rank ? &tm.w3b : &tm.w1b, fb, 0, (q - 20) * 64, 16 + tj, 3);
                } else {
                    if (q == 30) mbar_wait(tfree, 0);
                    const int c = q - 30;
                    const int f0 = (c < 8) ? 512 * kh + 128 * (c & 3) + 64 * (c >> 2) : 1024 + 256 * kh + 64 * (c - 8);
                    mbar_expect_tx(fb, 20480);
                    tma_load_3d_mc(dst + rank * 10240, &tm.w2, fb, 0, f0 + 32 * rank, 5 * nt, 3);
                }
            }
        } else if (warp == 1 && lane == 0) {
            for (int q = 0; q < 42; q++) {
                const int s = q % F_NS, use = q / F_NS;
                if (q >= 30 && ((q - 30) & 3) == 0) {
                    mbar_wait(gready + 8 * ((q - 30) >> 2), 0);
                }
                if (use > 0) mbar_wait(empty + 8 * s, (use - 1) & 1);
                const uint32_t dst = sbase + s * F_SLOT, fb = full + 8 * s;
                if (q == 0) { pdl_wait(); }
                if (q < 20) {
                    mbar_expect_tx(fb, 8192);
                    tma_load_2d(dst, &tm.hnA, fb, q * 32, ti * 128);
                } else if (q < 30) {
                    mbar_expect_tx(fb, 16384);
                    tma_load_2d(dst, &tm.hnB, fb, (q - 20) * 64, ti * 128);
                } else {
                    const int c = q - 30;
                    const int f0 = (c < 8) ? 512 * kh + 128 * (c & 3) + 64 * (c >> 2) : 1024 + 256 * kh + 64 * (c - 8);
                    mbar_expect_tx(fb, 16384);
                    tma_load_2d(dst, &tm.g, fb, f0, ti * 128);
                }
            }
        } else if (warp == 2 && lane == 0) {
            auto store = [&](int cw, int n) {
                const int col = (n < 4) ? 128 * tj + 32 * n : 1024 + 64 * tj + 32 * (n - 4);
                mbar_wait(sfull + 48 * cw + 8 * n, 0);
                asm volatile("cp.async.bulk.tensor.2d.global.shared::cta.bulk_group [%0, {%2, %3}], [%1];" ::"l"(&tm.gst), "r"(kf_stg(sbase, cw, n)), "r"(col), "r"(ti * 128 + cw * 64) : "memory");
                asm volatile("cp.async.bulk.commit_group;" ::: "memory");
            };
            auto publish = [&](int i) {
                asm volatile("cp.async.bulk.wait_group 0;" ::: "memory");
                asm volatile("red.relaxed.gpu.global.add.u32 [%0], 1;" ::"l"(&g_flags[((ti * 2 + kh) * 3 + i) * 32]) : "memory");
            };
            store(0, 0); store(1, 0); store(0, 1); store(1, 1);
            publish(0);
            store(0, 2); store(1, 2); store(0, 3); store(1, 3);
            publish(1);
            arrive_both(tfree);
            mbar_arrive(sfree);
            __threadfence();
            atomicAdd(&g_flags[96 * 32 + blockIdx.x], 1u);
            store(0, 4); store(0, 5);
            asm volatile("cp.async.bulk.wait_group.read 0;" ::: "memory");
            mbar_arrive(sfree + 8);
            store(1, 4); store(1, 5);
            publish(2);
        } else if (warp == 3 && lane == 0) {
            pdl_wait();
            for (int i = 0; i < 3; i++) {
                const unsigned* p = &g_flags[((ti * 2 + kh) * 3 + i) * 32];
                unsigned v;
                int spins = 0;
                do { asm volatile("ld.acquire.gpu.global.u32 %0, [%1];" : "=r"(v) : "l"(p) : "memory"); } while (v < 4 && ++spins < (1 << 24));
                asm volatile("fence.proxy.async.global;" ::: "memory");
                mbar_arrive(gready + 8 * i);
                if (i == 1) {
                    wait_flag(&g_flags[96 * 32 + (blockIdx.x ^ 8)], 1);
                    mbar_arrive(gready + 24);
                }
            }
        }
    } else {
        reg_alloc<232>();
        const int cw = wg - 1;
        const int lane = threadIdx.x & 31, warp = (threadIdx.x >> 5) & 3;
        const int t = lane & 3;
        const bool elected = (threadIdx.x & 127) == 0;
        const int grow0 = ti * 128 + cw * 64 + 16 * warp + (lane >> 2);
        uint4* inbox = g_part + ((blockIdx.x ^ 8) * 10) * 256 + (threadIdx.x - 128);
        const uint32_t dl = (sbase & 0x3FFFF) >> 4;
        auto mk = [](uint32_t lo, uint32_t hi) { return (uint64_t)lo | ((uint64_t)hi << 32); };
        float accA[128];
        for (int q = 0; q < 20; q++) {
            const int s = q % F_NS, ph = (q / F_NS) & 1;
            mbar_wait(full + 8 * s, ph);
            const uint32_t sa = sbase + s * F_SLOT + cw * 4096, sb = sbase + s * F_SLOT + 16384;
            wgmma_fence();
#pragma unroll
            for (int k = 0; k < 2; k++)
                wgmma_ss_bf16_n256<0, 1>(accA, make_desc(sa + k * 32, 16, 512, 2), make_desc(sb + k * 2048, 4096, 1024, 1), (q | k) != 0);
            wgmma_commit();
            wgmma_wait<1>();
            if (q > 0 && elected) arrive_both(empty + 8 * ((q - 1) % F_NS));
            if (q >= 6 && q < 11) __stcg(inbox + (q - 6) * 256, make_uint4(0u, 0u, 0u, 0u));
        }
        wgmma_wait<0>();
        fence_regs<128>(accA);
        if (elected) arrive_both(empty + 8 * (19 % F_NS));
        float accB[64];
        silu_guard<64, 64>(accA);
        uint32_t wo0, wo1;
        {
            const int row = 16 * warp + (lane & 7) + (lane & 8), jo = lane >> 4, sw = (row >> 1) & 3;
            wo0 = row * 64 + ((jo ^ sw) << 4);
            wo1 = row * 64 + (((2 + jo) ^ sw) << 4);
        }
        const uint32_t bfull = sfull + 48 * cw;
#define KF_STAGE_B(i2)                                                                                                                     \
        {                                                                                                                                  \
            const int q = 20 + (i2);                                                                                                       \
            const int s = q % F_NS, ph = (q / F_NS) & 1;                                                                                   \
            mbar_wait(full + 8 * s, ph);                                                                                                   \
            const uint32_t la = dl + s * (F_SLOT / 16) + cw * 512 + (1u << 16), lb = dl + s * (F_SLOT / 16) + 1024 + (512u << 16);         \
            wgmma_fence();                                                                                                                 \
            _Pragma("unroll") for (int k = 0; k < 4; k++)                                                                                  \
                wgmma_ss_bf16_n128<0, 1>(accB, mk(la + k * 2, 64u | (1u << 30)), mk(lb + k * 128, 64u | (1u << 30)), ((i2) | k) != 0);     \
            wgmma_commit();                                                                                                                \
            wgmma_wait<1>();                                                                                                               \
            if ((i2) > 0 && elected) arrive_both(empty + 8 * ((q - 1) % F_NS));                                                            \
        }
        {
            epi1_q<0, 64, false>(accA, kf_stg(sbase, cw, 0), wo0, wo1, 0, bfull + 0, lane);
            epi1_q<1, 64, false>(accA, kf_stg(sbase, cw, 1), wo0, wo1, 0, bfull + 8, lane);
            epi1_q<2, 64, false>(accA, kf_stg(sbase, cw, 2), wo0, wo1, 0, bfull + 16, lane);
            epi1_q<3, 64, false>(accA, kf_stg(sbase, cw, 3), wo0, wo1, 0, bfull + 24, lane);
            KF_STAGE_B(0)
            KF_STAGE_B(1)
            KF_STAGE_B(2)
            KF_STAGE_B(3)
            KF_STAGE_B(4)
            KF_STAGE_B(5)
            KF_STAGE_B(6)
            KF_STAGE_B(7)
            KF_STAGE_B(8)
            KF_STAGE_B(9)
        }
        wgmma_wait<0>();
        fence_regs<64>(accB);
        silu_guard<32, 32>(accB);
        if (elected) arrive_both(empty + 8 * (29 % F_NS));
        float acc[80];
#define KF_STAGE_2(c)                                                                                                                      \
        {                                                                                                                                  \
            const int q = 30 + (c);                                                                                                        \
            const int s = q % F_NS, ph = (q / F_NS) & 1;                                                                                   \
            mbar_wait(full + 8 * s, ph);                                                                                                   \
            const uint32_t la = dl + s * (F_SLOT / 16) + cw * 512 + (1u << 16), lb = dl + s * (F_SLOT / 16) + 1024 + (128u << 16);         \
            wgmma_fence();                                                                                                                 \
            _Pragma("unroll") for (int k = 0; k < 4; k++)                                                                                  \
                wgmma_ss_bf16_n160<0, 1>(acc, mk(la + k * 2, 64u | (1u << 30)), mk(lb + (k >> 1) * 640 + (k & 1) * 64, 32u | (2u << 30)), ((c) | k) != 0); \
            wgmma_commit();                                                                                                                \
            wgmma_wait<1>();                                                                                                               \
            if ((c) > 0 && (c) < 7 && elected) arrive_both(empty + 8 * ((q - 1) % F_NS));                                                  \
        }
#pragma unroll 1
        for (int ph2 = 0; ph2 < 2; ph2++) {
            if (ph2 == cw) {
                epi1_q<0, 32, true>(accB, kf_stg(sbase, cw, 4), wo0, wo1, sfree + 8 * cw, bfull + 32, lane);
                epi1_q<1, 32, false>(accB, kf_stg(sbase, cw, 5), wo0, wo1, 0, bfull + 40, lane);
            } else {
                KF_STAGE_2(0)
                KF_STAGE_2(1)
            }
        }
        uint4 hv[5];
        const int c0 = nt * 160;
        const int orow = grow0 + 8 * kh;
#pragma unroll
        for (int q = 0; q < 5; q++) hv[q] = __ldcg(reinterpret_cast<const uint4*>(g_h + orow * 640 + c0 + 32 * q + 8 * t));
#pragma unroll 1
        for (int c = 2; c < 12; c++) {
            KF_STAGE_2(c)
        }
        wgmma_wait<0>();
        fence_regs<80>(acc);
        mbar_wait(gready + 24, 0);
        {
            const int ctid = threadIdx.x - 128;
            uint4* dst = g_part + (blockIdx.x * 10) * 256 + ctid;
            uint4* src = g_part + ((blockIdx.x ^ 8) * 10) * 256 + ctid;
            float keep[40];
#pragma unroll
            for (int p = 0; p < 5; p++) {
                uint32_t w[4];
#pragma unroll
                for (int i = 0; i < 4; i++) {
                    const int j = 4 * p + i;
                    const uint32_t v = kh ? pack_bf16(acc[4 * j], acc[4 * j + 1]) : pack_bf16(acc[4 * j + 2], acc[4 * j + 3]);
                    w[i] = v ? v : 1u;
                    keep[2 * j] = kh ? acc[4 * j + 2] : acc[4 * j];
                    keep[2 * j + 1] = kh ? acc[4 * j + 3] : acc[4 * j + 1];
                }
                __stcg(dst + p * 256, make_uint4(w[0], w[1], w[2], w[3]));
            }
            uint4 pv[5];
            int spins = 0;
            while (true) {
                bool ok = true;
#pragma unroll
                for (int p = 0; p < 5; p++)
                    asm volatile("ld.relaxed.gpu.global.v4.u32 {%0, %1, %2, %3}, [%4];" : "=r"(pv[p].x), "=r"(pv[p].y), "=r"(pv[p].z), "=r"(pv[p].w) : "l"(src + p * 256) : "memory");
#pragma unroll
                for (int p = 0; p < 5; p++) ok = ok && pv[p].x && pv[p].y && pv[p].z && pv[p].w;
                if (__all_sync(0xffffffffu, ok) || ++spins > (1 << 20)) break;
            }
#pragma unroll
            for (int q = 0; q < 5; q++) {
                const uint32_t pw[4] = {pv[q].x, pv[q].y, pv[q].z, pv[q].w};
                uint32_t r[4];
#pragma unroll
                for (int i = 0; i < 4; i++) r[i] = pack_bf16(keep[2 * (4 * q + i)] + bf_lo(pw[i]), keep[2 * (4 * q + i) + 1] + bf_hi(pw[i]));
                uint4 o = quad_transpose(r[0], r[1], r[2], r[3], t);
                o.x = hadd2_bf16(hv[q].x, o.x); o.y = hadd2_bf16(hv[q].y, o.y); o.z = hadd2_bf16(hv[q].z, o.z); o.w = hadd2_bf16(hv[q].w, o.w);
                *reinterpret_cast<uint4*>(out + orow * 640 + c0 + 32 * q + 8 * t) = o;
            }
        }
    }
    asm volatile("barrier.cluster.arrive.relaxed.aligned;\nbarrier.cluster.wait.aligned;" ::: "memory");
}

typedef CUresult (*PFN_encodeTiled)(CUtensorMap*, CUtensorMapDataType, cuuint32_t, void*, const cuuint64_t*, const cuuint64_t*, const cuuint32_t*,
                                    const cuuint32_t*, CUtensorMapInterleave, CUtensorMapSwizzle, CUtensorMapL2promotion, CUtensorMapFloatOOBfill);
static CUtensorMap make_tmap(PFN_encodeTiled fn, void* base, int rank, const uint64_t* dims, const uint64_t* strides_bytes, const uint32_t* box, CUtensorMapSwizzle swz,
                             CUtensorMapL2promotion promo = CU_TENSOR_MAP_L2_PROMOTION_L2_128B) {
    CUtensorMap m;
    cuuint64_t gd[5], gs[5];
    cuuint32_t bx[5], es[5];
    for (int i = 0; i < rank; i++) { gd[i] = dims[i]; bx[i] = box[i]; es[i] = 1; }
    for (int i = 0; i < rank - 1; i++) gs[i] = strides_bytes[i];
    fn(&m, CU_TENSOR_MAP_DATA_TYPE_BFLOAT16, rank, base, gd, gs, bx, es, CU_TENSOR_MAP_INTERLEAVE_NONE, swz, promo, CU_TENSOR_MAP_FLOAT_OOB_FILL_NONE);
    return m;
}
template <typename... KArgs, typename... Args>
static void launch(void (*kern)(KArgs...), int grid, int block, int smem, bool pdl, Args... args) {
    cudaLaunchConfig_t cfg = {};
    cfg.gridDim = dim3(grid); cfg.blockDim = dim3(block); cfg.dynamicSmemBytes = smem; cfg.stream = cudaStreamPerThread;
    cudaLaunchAttribute at[1];
    at[0].id = cudaLaunchAttributeProgrammaticStreamSerialization;
    at[0].val.programmaticStreamSerializationAllowed = 1;
    cfg.attrs = at; cfg.numAttrs = pdl ? 1 : 0;
    cudaLaunchKernelEx(&cfg, kern, args...);
}


static void make_kf_maps(PFN_encodeTiled fn, KfMaps& m, void* hn, void* gg, void* w1, void* w3, void* w2) {
    { uint64_t d[2] = {640, 2048}, s[1] = {1280}; uint32_t b[2] = {32, 128}; m.hnA = make_tmap(fn, hn, 2, d, s, b, CU_TENSOR_MAP_SWIZZLE_64B); }
    { uint64_t d[2] = {640, 2048}, s[1] = {1280}; uint32_t b[2] = {64, 128}; m.hnB = make_tmap(fn, hn, 2, d, s, b, CU_TENSOR_MAP_SWIZZLE_128B); }
    { uint64_t d[3] = {64, 640, 24}, s[2] = {3072, 128}; uint32_t b[3] = {64, 32, 2};
      m.w1a = make_tmap(fn, w1, 3, d, s, b, CU_TENSOR_MAP_SWIZZLE_128B); m.w3a = make_tmap(fn, w3, 3, d, s, b, CU_TENSOR_MAP_SWIZZLE_128B); }
    { uint64_t d[3] = {64, 640, 24}, s[2] = {3072, 128}; uint32_t b[3] = {64, 64, 1};
      m.w1b = make_tmap(fn, w1, 3, d, s, b, CU_TENSOR_MAP_SWIZZLE_128B); m.w3b = make_tmap(fn, w3, 3, d, s, b, CU_TENSOR_MAP_SWIZZLE_128B); }
    { uint64_t d[2] = {1536, 2048}, s[1] = {3072}; uint32_t b[2] = {64, 128}; m.g = make_tmap(fn, gg, 2, d, s, b, CU_TENSOR_MAP_SWIZZLE_128B); }
    { uint64_t d[2] = {1536, 2048}, s[1] = {3072}; uint32_t b[2] = {32, 64}; m.gst = make_tmap(fn, gg, 2, d, s, b, CU_TENSOR_MAP_SWIZZLE_64B); }
    { uint64_t d[3] = {32, 1536, 20}, s[2] = {1280, 64}; uint32_t b[3] = {32, 32, 5}; m.w2 = make_tmap(fn, w2, 3, d, s, b, CU_TENSOR_MAP_SWIZZLE_64B); }
}

extern "C" void kernel_launch(void* const* d_in, const int* in_sizes, int n_in, void* d_out, int out_size) {
    const bf16* x = (const bf16*)d_in[0];
    const bf16* wr = (const bf16*)d_in[1];
    const bf16* wi = (const bf16*)d_in[2];
    bf16* w1 = (bf16*)d_in[4];
    bf16* w3 = (bf16*)d_in[5];
    bf16* w2 = (bf16*)d_in[6];
    static bool init = false;
    static KfMaps maps;
    static FftMaps fmaps;
    static void* cached_ptrs[5] = {nullptr, nullptr, nullptr, nullptr, nullptr};
    if (!init || cached_ptrs[0] != w1 || cached_ptrs[1] != w3 || cached_ptrs[2] != w2 || cached_ptrs[3] != (void*)wr || cached_ptrs[4] != (void*)wi) {
        void* p = nullptr;
        cudaDriverEntryPointQueryResult st;
        cudaGetDriverEntryPoint("cuTensorMapEncodeTiled", &p, cudaEnableDefault, &st);
        PFN_encodeTiled fn = (PFN_encodeTiled)p;
        void *hn, *gg, *vv;
        cudaGetSymbolAddress(&vv, g_V);
        cudaGetSymbolAddress(&hn, g_hn);
        cudaGetSymbolAddress(&gg, g_g);
        make_kf_maps(fn, maps, hn, gg, w1, w3, w2);
        { uint64_t d[4] = {2568, 4, 16, 4}, s[3] = {5136, 4 * 5136, 64 * 5136}; uint32_t b[4] = {168, 1, 4, 4};
          fmaps.wr = make_tmap(fn, (void*)wr, 4, d, s, b, CU_TENSOR_MAP_SWIZZLE_NONE); fmaps.wi = make_tmap(fn, (void*)wi, 4, d, s, b, CU_TENSOR_MAP_SWIZZLE_NONE); }
        { uint64_t d[4] = {16, 32, 20, 128}, s[3] = {20 * 4096, 4096, 32}; uint32_t b[4] = {16, 32, 5, 1}; fmaps.v = make_tmap(fn, vv, 4, d, s, b, CU_TENSOR_MAP_SWIZZLE_NONE, CU_TENSOR_MAP_L2_PROMOTION_NONE); }
        cudaFuncSetAttribute(k1_ln_fft, cudaFuncAttributeMaxDynamicSharedMemorySize, K1_SMEM);
        cudaFuncSetAttribute(k2_colfft, cudaFuncAttributeMaxDynamicSharedMemorySize, K2_SMEM);
        cudaFuncSetAttribute(k3_ifft_ln, cudaFuncAttributeMaxDynamicSharedMemorySize, K3_SMEM);
        cudaFuncSetAttribute(kf_ffn, cudaFuncAttributeMaxDynamicSharedMemorySize, F_SMEM);
        cudaFuncSetAttribute(k1_ln_fft, cudaFuncAttributePreferredSharedMemoryCarveout, cudaSharedmemCarveoutMaxShared);
        cudaFuncSetAttribute(k2_colfft, cudaFuncAttributePreferredSharedMemoryCarveout, cudaSharedmemCarveoutMaxShared);
        cudaFuncSetAttribute(k3_ifft_ln, cudaFuncAttributePreferredSharedMemoryCarveout, cudaSharedmemCarveoutMaxShared);
        cudaFuncSetAttribute(kf_ffn, cudaFuncAttributePreferredSharedMemoryCarveout, cudaSharedmemCarveoutMaxShared);
        cached_ptrs[0] = w1; cached_ptrs[1] = w3; cached_ptrs[2] = w2; cached_ptrs[3] = (void*)wr; cached_ptrs[4] = (void*)wi;
        init = true;
    }
    launch(k1_ln_fft, 128, 512, K1_SMEM, false, x, fmaps);
    launch(k2_colfft, 107, 384, K2_SMEM, true, (const uint8_t*)w1, (const uint8_t*)w3, (const uint8_t*)w2);
    launch(k3_ifft_ln, 128, 512, K3_SMEM, true, x, fmaps);
    launch(kf_ffn, 128, 384, F_SMEM, true, maps, (bf16*)d_out);
}
```
